```python
import torch

def _softmax(x, axis=-1):
    return torch.softmax(x, dim=axis)
def _gelu(x):
    return torch.nn.functional.gelu(x, approximate="tanh")
def _silu(x):
    return torch.nn.functional.silu(x)
def _sigmoid(x):
    return torch.sigmoid(x)
def _layernorm(x, axis=-1, eps=1e-5):
    m = x.mean(dim=axis, keepdim=True)
    v = x.var(dim=axis, keepdim=True, unbiased=False)
    return (x - m) / torch.sqrt(v + eps)
def _scatter_add(tgt, idx, src, axis=0):
    return tgt.clone().index_add_(axis, idx, src)
def _segment_sum(src, seg, n):
    out = torch.zeros((n,) + src.shape[1:], dtype=src.dtype)
    return out.index_add_(0, seg, src)
def _pad(x, pw):
    flat = tuple(v for pair in reversed(pw) for v in pair)
    return torch.nn.functional.pad(x, flat)

kernel_name = 'standalone__gqa_block_cached__near_ridge'

def setup_inputs():

    _w = (lambda a: (lambda t: t.to(torch.bfloat16) if t.is_floating_point() else t)(torch.as_tensor(a)))
    B, Sq, D = 32, 160, 640
    Hq, Hkv, Sk, Dh = 32, 32, 512, 128
    assert Hq % Hkv == 0, (Hq, Hkv)
    return {
        "x": _w((lambda *s: torch.randn(*s, dtype=torch.bfloat16) * 0.8)(B, Sq, D)),
        "k_cache": _w((lambda *s: torch.randn(*s, dtype=torch.bfloat16) * 0.8)(B, Hkv, Sk, Dh)),
        "v_cache": _w((lambda *s: torch.randn(*s, dtype=torch.bfloat16) * 0.05)(B, Hkv, Sk, Dh)),
        "wq": _w((lambda *s: torch.randn(*s, dtype=torch.bfloat16) * 0.8)(D, Hq * Dh) * (D ** -0.5)),
        "wo": _w((lambda *s: torch.randn(*s, dtype=torch.bfloat16) * 0.05)(Hq * Dh, D) * ((Hq * Dh) ** -0.5)),
    }

def reference(x, k_cache, v_cache, wq, wo):
    B, Sq, D = x.shape
    Hq, Dh = 32, 128
    Hkv = k_cache.shape[1]
    rep = Hq // Hkv
    q = (lambda x, *d: x.permute(*d))((x @ wq).reshape(B, Sq, Hq, Dh), 0, 2, 1, 3)
    k = (lambda x, n, axis: torch.repeat_interleave(x, n, dim=axis))(k_cache, rep, axis=1)
    v = (lambda x, n, axis: torch.repeat_interleave(x, n, dim=axis))(v_cache, rep, axis=1)
    scores = torch.einsum("bhqd,bhkd->bhqk", q, k) * (Dh ** -0.5)
    p = _softmax(scores, axis=-1)
    o = torch.einsum("bhqk,bhkd->bhqd", p, v)
    return (lambda x, *d: x.permute(*d))(o, 0, 2, 1, 3).reshape(B, Sq, Hq * Dh) @ wo
```

```cpp
#include <cuda_runtime.h>
#include <cuda_bf16.h>
#include <cuda.h>
#include <stdint.h>

namespace {

constexpr int NB = 32, SQ = 160, DM = 640, NH = 32, SK = 512, DH = 128;
constexpr int NITEMS = NB * NH;

constexpr int A_STAGE = 36864;
constexpr int A_NST = 5;
constexpr int A_STG_OFF = A_STAGE * A_NST;
constexpr int P_STAGE = 57344;
constexpr int P_NST = 4;
constexpr int BAR_OFF = P_STAGE * P_NST;
constexpr int SMEM_BYTES = BAR_OFF + 256 + 1408 + 1024;

__device__ __nv_bfloat16 g_O[(size_t)NITEMS * SQ * DH];
__device__ unsigned int g_flags[NITEMS];
__device__ unsigned int g_epoch;
__device__ unsigned int g_done;
__device__ unsigned int g_next;

#define PROF_T(idx)
#define PROF_D(idx)
#define PROF_G(idx)
#define PROF_DUMP()
#define PROF_CLR()
__device__ __forceinline__ uint32_t smem_u32(const void* p) { return (uint32_t)__cvta_generic_to_shared(p); }
__device__ __forceinline__ uint64_t make_desc(uint32_t addr, uint32_t lbo, uint32_t sbo) {
  return (uint64_t)((addr & 0x3FFFF) >> 4) | ((uint64_t)(lbo >> 4) << 16) | ((uint64_t)(sbo >> 4) << 32) | ((uint64_t)1 << 62);
}
__device__ __forceinline__ void mbar_init(uint32_t bar, int cnt) {
  asm volatile("mbarrier.init.shared::cta.b64 [%0], %1;" ::"r"(bar), "r"(cnt));
}
__device__ __forceinline__ void mbar_expect_tx(uint32_t bar, uint32_t bytes) {
  asm volatile("mbarrier.arrive.expect_tx.shared::cta.b64 _, [%0], %1;" ::"r"(bar), "r"(bytes) : "memory");
}
__device__ __forceinline__ void mbar_arrive(uint32_t bar) {
  asm volatile("mbarrier.arrive.shared::cta.b64 _, [%0];" ::"r"(bar) : "memory");
}
__device__ __forceinline__ bool mbar_try(uint32_t bar, uint32_t parity) {
  uint32_t done;
  asm volatile("{\n.reg .pred p;\nmbarrier.try_wait.parity.shared::cta.b64 p, [%1], %2;\nselp.u32 %0, 1, 0, p;\n}"
               : "=r"(done) : "r"(bar), "r"(parity) : "memory");
  return done != 0;
}
__device__ __forceinline__ bool deadline_passed() {
  extern __shared__ uint8_t smem_raw[];
  const uint32_t a = ((smem_u32(smem_raw) + 1023) & ~1023u) + BAR_OFF + 248;
  uint32_t t0, t1;
  asm volatile("ld.shared.u32 %0, [%1];" : "=r"(t0) : "r"(a) : "memory");
  asm volatile("mov.u32 %0, %globaltimer_lo;" : "=r"(t1));
  return (t1 - t0) > 200000000u;
}
__device__ __forceinline__ void mbar_wait(uint32_t bar, uint32_t parity) {
  if (mbar_try(bar, parity)) return;
  while (!mbar_try(bar, parity)) {
    if (deadline_passed()) break;
  }
}
__device__ __forceinline__ void tma_load_2d(uint32_t dst, const CUtensorMap* m, int c0, int c1, uint32_t bar) {
  asm volatile("cp.async.bulk.tensor.2d.shared::cluster.global.mbarrier::complete_tx::bytes [%0], [%1, {%3, %4}], [%2];"
               ::"r"(dst), "l"(m), "r"(bar), "r"(c0), "r"(c1) : "memory");
}
__device__ __forceinline__ void tma_load_3d(uint32_t dst, const CUtensorMap* m, int c0, int c1, int c2, uint32_t bar) {
  asm volatile("cp.async.bulk.tensor.3d.shared::cluster.global.mbarrier::complete_tx::bytes [%0], [%1, {%3, %4, %5}], [%2];"
               ::"r"(dst), "l"(m), "r"(bar), "r"(c0), "r"(c1), "r"(c2) : "memory");
}
__device__ __forceinline__ void tma_load_3d_hint(uint32_t dst, const CUtensorMap* m, int c0, int c1, int c2, uint32_t bar, uint64_t pol) {
  asm volatile("cp.async.bulk.tensor.3d.shared::cluster.global.mbarrier::complete_tx::bytes.L2::cache_hint [%0], [%1, {%3, %4, %5}], [%2], %6;"
               ::"r"(dst), "l"(m), "r"(bar), "r"(c0), "r"(c1), "r"(c2), "l"(pol) : "memory");
}
__device__ __forceinline__ void tma_store_3d(const CUtensorMap* m, int c0, int c1, int c2, uint32_t src) {
  asm volatile("cp.async.bulk.tensor.3d.global.shared::cta.bulk_group [%0, {%2, %3, %4}], [%1];"
               ::"l"(m), "r"(src), "r"(c0), "r"(c1), "r"(c2) : "memory");
}
__device__ __forceinline__ void wg_fence() { asm volatile("wgmma.fence.sync.aligned;" ::: "memory"); }
__device__ __forceinline__ void wg_commit() { asm volatile("wgmma.commit_group.sync.aligned;" ::: "memory"); }
template <int N> __device__ __forceinline__ void wg_wait() { asm volatile("wgmma.wait_group.sync.aligned %0;" ::"n"(N) : "memory"); }
__device__ __forceinline__ void fence_async_smem() { asm volatile("fence.proxy.async.shared::cta;" ::: "memory"); }
__device__ __forceinline__ void named_bar(int id, int n) { asm volatile("bar.sync %0, %1;" ::"r"(id), "r"(n) : "memory"); }
__device__ __forceinline__ uint32_t tid_now() { uint32_t t; asm volatile("mov.u32 %0, %tid.x;" : "=r"(t)); return t; }
__device__ __forceinline__ void arrive_lane0(uint32_t bar) {
  asm volatile("{\n.reg .pred p;\nelect.sync _|p, 0xffffffff;\n@p mbarrier.arrive.shared::cta.b64 _, [%0];\n}" ::"r"(bar) : "memory");
}
__device__ __forceinline__ float rcp(float x) { float y; asm("rcp.approx.ftz.f32 %0, %1;" : "=f"(y) : "f"(x)); return y; }
__device__ __forceinline__ float ex2(float x) { float y; asm("ex2.approx.ftz.f32 %0, %1;" : "=f"(y) : "f"(x)); return y; }
__device__ __forceinline__ uint32_t pack_bf16(float lo, float hi) {
  uint32_t r; asm("cvt.rn.bf16x2.f32 %0, %1, %2;" : "=r"(r) : "f"(hi), "f"(lo)); return r;
}
__device__ __forceinline__ void stsm_x4(uint32_t addr, uint32_t r0, uint32_t r1, uint32_t r2, uint32_t r3) {
  asm volatile("stmatrix.sync.aligned.m8n8.x4.shared.b16 [%0], {%1, %2, %3, %4};" ::"r"(addr), "r"(r0), "r"(r1), "r"(r2), "r"(r3) : "memory");
}

#define ACC_STR                                                                        \
  "{%0, %1, %2, %3, %4, %5, %6, %7, %8, %9, %10, %11, %12, %13, %14, %15, "            \
  "%16, %17, %18, %19, %20, %21, %22, %23, %24, %25, %26, %27, %28, %29, %30, %31, "   \
  "%32, %33, %34, %35, %36, %37, %38, %39, %40, %41, %42, %43, %44, %45, %46, %47, "   \
  "%48, %49, %50, %51, %52, %53, %54, %55, %56, %57, %58, %59, %60, %61, %62, %63}, "
#define ACC8(C, d, o) C(d[o]), C(d[o + 1]), C(d[o + 2]), C(d[o + 3]), C(d[o + 4]), C(d[o + 5]), C(d[o + 6]), C(d[o + 7])
#define ACC_OPS(C, d) ACC8(C, d, 0), ACC8(C, d, 8), ACC8(C, d, 16), ACC8(C, d, 24), ACC8(C, d, 32), ACC8(C, d, 40), ACC8(C, d, 48), ACC8(C, d, 56)

template <int TB, bool INIT>
__device__ __forceinline__ void wgmma_ss(float (&d)[64], uint64_t da, uint64_t db) {
  if constexpr (INIT) {
    asm volatile("wgmma.mma_async.sync.aligned.m64n128k16.f32.bf16.bf16 " ACC_STR "%64, %65, 0, 1, 1, 0, %66;"
                 : ACC_OPS("=f", d) : "l"(da), "l"(db), "n"(TB));
  } else {
    asm volatile("wgmma.mma_async.sync.aligned.m64n128k16.f32.bf16.bf16 " ACC_STR "%64, %65, 1, 1, 1, 0, %66;"
                 : ACC_OPS("+f", d) : "l"(da), "l"(db), "n"(TB));
  }
}
template <int TB, bool INIT>
__device__ __forceinline__ void wgmma_rs(float (&d)[64], uint32_t a0, uint32_t a1, uint32_t a2, uint32_t a3, uint64_t db) {
  if constexpr (INIT) {
    asm volatile("wgmma.mma_async.sync.aligned.m64n128k16.f32.bf16.bf16 " ACC_STR "{%64, %65, %66, %67}, %68, 0, 1, 1, %69;"
                 : ACC_OPS("=f", d) : "r"(a0), "r"(a1), "r"(a2), "r"(a3), "l"(db), "n"(TB));
  } else {
    asm volatile("wgmma.mma_async.sync.aligned.m64n128k16.f32.bf16.bf16 " ACC_STR "{%64, %65, %66, %67}, %68, 1, 1, 1, %69;"
                 : ACC_OPS("+f", d) : "r"(a0), "r"(a1), "r"(a2), "r"(a3), "l"(db), "n"(TB));
  }
}

template <int TB, bool INIT>
__device__ __forceinline__ void wgmma_sp(float (&d)[64], uint32_t a0, uint32_t a1, uint32_t a2, uint32_t a3, uint64_t db, uint32_t meta) {
  if constexpr (INIT) {
    asm volatile("wgmma.mma_async.sp.sync.aligned.m64n128k32.f32.bf16.bf16 " ACC_STR "{%64, %65, %66, %67}, %68, %69, 0, 0, 1, 1, %70;"
                 : ACC_OPS("=f", d) : "r"(a0), "r"(a1), "r"(a2), "r"(a3), "l"(db), "r"(meta), "n"(TB));
  } else {
    asm volatile("wgmma.mma_async.sp.sync.aligned.m64n128k32.f32.bf16.bf16 " ACC_STR "{%64, %65, %66, %67}, %68, %69, 0, 1, 1, 1, %70;"
                 : ACC_OPS("+f", d) : "r"(a0), "r"(a1), "r"(a2), "r"(a3), "l"(db), "r"(meta), "n"(TB));
  }
}
__device__ __forceinline__ bool wg_any(int id, bool v) {
  uint32_t r;
  asm volatile("{\n.reg .pred p, q;\nsetp.ne.u32 q, %2, 0;\nbarrier.cta.red.or.pred p, %1, 128, q;\nselp.u32 %0, 1, 0, p;\n}"
               : "=r"(r) : "r"(id), "r"((uint32_t)v) : "memory");
  return __shfl_sync(0xffffffffu, r, 0) != 0;
}
#define SPLIT 12
#define TOK_WAIT(w) do { mbar_wait(bar + B_TOK + 8 * (w), tph); tph ^= 1; } while (0)
#define TOK_PASS(w) arrive_lane0(bar + B_TOK + 8 * (w))
__device__ __forceinline__ int lds_s32(uint32_t a) { int v; asm volatile("ld.shared.s32 %0, [%1];" : "=r"(v) : "r"(a) : "memory"); return v; }
__device__ __forceinline__ void sts_s32(uint32_t a, int v) { asm volatile("st.shared.s32 [%0], %1;" ::"r"(a), "r"(v) : "memory"); }
__device__ __forceinline__ void lds_v2(uint32_t a, uint32_t& x, uint32_t& y) {
  asm volatile("ld.shared.v2.u32 {%0, %1}, [%2];" : "=r"(x), "=r"(y) : "r"(a) : "memory");
}

__device__ __forceinline__ void item_bh(int i, int& b, int& h) {
  b = ((i >> 9) << 4) + (i & 15);
  h = (i & 511) >> 4;
}

struct Sched {
  int n_p;
  int zero;
};

template <int N> __device__ __forceinline__ void fence_regs(float (&d)[N]) {
#pragma unroll
  for (int i = 0; i < N; i++) asm volatile("" : "+f"(d[i])::"memory");
}
constexpr int Y_LIMIT_BITS = 0x41800000;
__device__ __forceinline__ float ex2v(float x) { float y; asm volatile("ex2.approx.ftz.f32 %0, %1;" : "=f"(y) : "f"(x)); return y; }
__device__ __forceinline__ void sched_boundary(const int zero) {
  for (int i = zero; i > 0; i--) asm volatile("nanosleep.u32 0;");
}

template <bool V> struct BoolC { static constexpr bool value = V; };

constexpr int B_AFULL = 0, B_AEMPTY = 40, B_PFULL = 80, B_PEMPTY = 112, B_OFULL = 144, B_OEMPTY = 168, B_ITEMQ = 192, B_TOK = 208;
constexpr float SM_SCALE = 0.08838834764831845f * 1.4426950408889634f;

__device__ __forceinline__ void a_dense(const uint32_t base, const int wg, const int zero, float (&accS)[64], float (&accO)[64]) {
  const uint32_t bar = base + BAR_OFF;
  const uint32_t a_full = bar + B_AFULL, a_empty = bar + B_AEMPTY;
  const uint32_t stg = base + A_STG_OFF + 8192 + wg * 16384;
  constexpr uint32_t hstride = 8192;
  const float cs = SM_SCALE;
  int st = 0; uint32_t ph = 0, tph = 0;
  if (wg == 1) TOK_PASS(2);
  for (int r = 0;; r++) {
    mbar_wait(a_full + 8 * st, ph);
    if (wg_any(1 + wg, lds_s32(bar + B_ITEMQ + (r & 3) * 4) < 0 || r >= 64)) {
      mbar_wait(bar + B_OEMPTY + 8 * wg, (r - 1) & 1);
      mbar_arrive(bar + B_OFULL + 8 * wg);
      break;
    }
    PROF_T(r * 3); PROF_D(40);
    int prev = 0;
    auto qstep = [&](auto first) {
      if (!decltype(first)::value) mbar_wait(a_full + 8 * st, ph);
      const uint32_t s = base + st * A_STAGE;
      const uint64_t da = make_desc(s + wg * 8192, 16, 1024);
      const uint64_t db = make_desc(s + 20480, 8192, 1024);
      wg_fence();
      wgmma_ss<1, decltype(first)::value>(accS, da, db);
#pragma unroll
      for (int kk = 1; kk < 4; kk++) wgmma_ss<1, false>(accS, da + kk * 2, db + kk * 128);
      wg_commit();
      if (!decltype(first)::value) {
        wg_wait<1>();
        arrive_lane0(a_empty + 8 * prev);
      }
      prev = st;
      if (++st == A_NST) { st = 0; ph ^= 1; }
    };
    qstep(BoolC<true>{});
#pragma unroll 1
    for (int c = 1; c < 10; c++) qstep(BoolC<false>{});
    wg_wait<0>();
    arrive_lane0(a_empty + 8 * prev);
    PROF_T(r * 3 + 1); PROF_D(41);
    if (r > 0) mbar_wait(bar + B_OEMPTY + 8 * wg, (r - 1) & 1);
    {
      const uint32_t t = tid_now();
      const uint32_t st_row = stg + ((t & 96) >> 1) * 128 + (t & 15) * 128;
      const uint32_t st_c = (t >> 4) & 1, st_x = t & 7;
#pragma unroll
      for (int j = 0; j < 16; j += 2) {
        const uint32_t ch = j + st_c;
        const uint32_t addr = st_row + (j >> 3) * hstride + (((ch & 7) ^ st_x) << 4);
        stsm_x4(addr, pack_bf16(accS[4 * j], accS[4 * j + 1]), pack_bf16(accS[4 * j + 2], accS[4 * j + 3]),
                pack_bf16(accS[4 * j + 4], accS[4 * j + 5]), pack_bf16(accS[4 * j + 6], accS[4 * j + 7]));
      }
    }
    fence_async_smem();
    named_bar(1 + wg, 128);
    float c0 = 0.f, c1 = 0.f, l0 = 0.f, l1 = 0.f;
#pragma unroll
    for (int j = 0; j < 64; j++) accO[j] = 0.f;
    const uint64_t dq0 = make_desc(stg, 16, 1024), dq1 = make_desc(stg + hstride, 16, 1024);
    uint64_t dk = make_desc(base + st * A_STAGE, 16, 1024);
    mbar_wait(a_full + 8 * st, ph);
    TOK_WAIT(wg);
#pragma unroll 1
    for (int jb = 0; jb < 4; jb++) {
      PROF_D(jb * 8 + 2);
      wg_fence();
      wgmma_ss<0, true>(accS, dq0, dk);
#pragma unroll
      for (int kk = 1; kk < 4; kk++) wgmma_ss<0, false>(accS, dq0 + kk * 2, dk + kk * 2);
#pragma unroll
      for (int kk = 0; kk < 4; kk++) wgmma_ss<0, false>(accS, dq1 + kk * 2, dk + 1024 + kk * 2);
      wg_commit();
      TOK_PASS(wg == 1 ? 0 : (jb == 0 ? 2 : 1));
      const uint32_t kbar = a_empty + 8 * st;
      if (++st == A_NST) { st = 0; ph ^= 1; }
      const uint64_t dv = make_desc(base + st * A_STAGE, 16384, 1024);
      PROF_D(jb * 8 + 3);
      wg_wait<0>();
      fence_regs(accS);
      PROF_D(jb * 8 + 4);
      arrive_lane0(kbar);
      if (jb == 0) {
        float x0 = fmaxf(accS[0], accS[1]), x1 = fmaxf(accS[2], accS[3]);
        float y0 = fmaxf(accS[4], accS[5]), y1 = fmaxf(accS[6], accS[7]);
#pragma unroll
        for (int j = 2; j < 16; j += 2) {
          x0 = fmaxf(x0, fmaxf(accS[4 * j], accS[4 * j + 1]));
          x1 = fmaxf(x1, fmaxf(accS[4 * j + 2], accS[4 * j + 3]));
          y0 = fmaxf(y0, fmaxf(accS[4 * j + 4], accS[4 * j + 5]));
          y1 = fmaxf(y1, fmaxf(accS[4 * j + 6], accS[4 * j + 7]));
        }
        x0 = fmaxf(x0, y0); x1 = fmaxf(x1, y1);
        x0 = fmaxf(x0, __shfl_xor_sync(0xffffffffu, x0, 1));
        x1 = fmaxf(x1, __shfl_xor_sync(0xffffffffu, x1, 1));
        x0 = fmaxf(x0, __shfl_xor_sync(0xffffffffu, x0, 2));
        x1 = fmaxf(x1, __shfl_xor_sync(0xffffffffu, x1, 2));
        c0 = -x0 * cs; c1 = -x1 * cs;
      }
      {
        int v0 = 0, v1 = 0;
#pragma unroll
        for (int j = 0; j < 16; j++) {
          accS[4 * j] = fmaf(accS[4 * j], cs, c0); accS[4 * j + 1] = fmaf(accS[4 * j + 1], cs, c0);
          accS[4 * j + 2] = fmaf(accS[4 * j + 2], cs, c1); accS[4 * j + 3] = fmaf(accS[4 * j + 3], cs, c1);
          v0 = __vimax3_s32(v0, __float_as_int(accS[4 * j]), __float_as_int(accS[4 * j + 1]));
          v1 = __vimax3_s32(v1, __float_as_int(accS[4 * j + 2]), __float_as_int(accS[4 * j + 3]));
        }
        if (__any_sync(0xffffffffu, max(v0, v1) > Y_LIMIT_BITS)) {
          float d0 = __int_as_float(v0), d1 = __int_as_float(v1);
          d0 = fmaxf(d0, __shfl_xor_sync(0xffffffffu, d0, 1));
          d1 = fmaxf(d1, __shfl_xor_sync(0xffffffffu, d1, 1));
          d0 = fmaxf(d0, __shfl_xor_sync(0xffffffffu, d0, 2));
          d1 = fmaxf(d1, __shfl_xor_sync(0xffffffffu, d1, 2));
          const float al0 = ex2(-d0), al1 = ex2(-d1);
          c0 -= d0; c1 -= d1; l0 *= al0; l1 *= al1;
#pragma unroll
          for (int j = 0; j < 16; j++) {
            accS[4 * j] -= d0; accS[4 * j + 1] -= d0; accS[4 * j + 2] -= d1; accS[4 * j + 3] -= d1;
            accO[4 * j] *= al0; accO[4 * j + 1] *= al0; accO[4 * j + 2] *= al1; accO[4 * j + 3] *= al1;
          }
        }
      }
      uint32_t p[32];
      float t0 = 0.f, t1 = 0.f;
#pragma unroll
      for (int j = 0; j < 4 * SPLIT; j++) accS[j] = ex2v(accS[j]);
      mbar_wait(a_full + 8 * st, ph);
#pragma unroll
      for (int j = 4 * SPLIT; j < 64; j++) accS[j] = ex2v(accS[j]);
#pragma unroll
      for (int j = 0; j < SPLIT - 1; j++) {
        l0 += accS[4 * j]; t0 += accS[4 * j + 1]; l1 += accS[4 * j + 2]; t1 += accS[4 * j + 3];
        p[2 * j] = pack_bf16(accS[4 * j], accS[4 * j + 1]);
        p[2 * j + 1] = pack_bf16(accS[4 * j + 2], accS[4 * j + 3]);
      }
      sched_boundary(zero);
#pragma unroll
      for (int j = SPLIT - 1; j < 16; j++) {
        p[2 * j] = pack_bf16(accS[4 * j], accS[4 * j + 1]);
        p[2 * j + 1] = pack_bf16(accS[4 * j + 2], accS[4 * j + 3]);
        l0 += accS[4 * j]; t0 += accS[4 * j + 1]; l1 += accS[4 * j + 2]; t1 += accS[4 * j + 3];
      }
      l0 += t0; l1 += t1;
      PROF_D(jb * 8 + 5);
      TOK_WAIT(wg);
      PROF_D(jb * 8 + 6);
      wg_fence();
#pragma unroll
      for (int kk = 0; kk < 8; kk++) wgmma_rs<1, false>(accO, p[4 * kk], p[4 * kk + 1], p[4 * kk + 2], p[4 * kk + 3], dv + kk * 128);
      wg_commit();
      TOK_PASS((wg == 0 && jb == 3) ? 1 : 2);
      PROF_D(jb * 8 + 7);
      const uint32_t vbar = a_empty + 8 * st;
      if (++st == A_NST) { st = 0; ph ^= 1; }
      dk = make_desc(base + st * A_STAGE, 16, 1024);
      if (jb < 3) {
        mbar_wait(a_full + 8 * st, ph);
        PROF_D(jb * 8 + 8);
        TOK_WAIT(wg);
        PROF_D(jb * 8 + 9);
      }
      wg_wait<0>();
      fence_regs(accO);
      PROF_D(32 + jb);
      arrive_lane0(vbar);
    }
    l0 += __shfl_xor_sync(0xffffffffu, l0, 1); l1 += __shfl_xor_sync(0xffffffffu, l1, 1);
    l0 += __shfl_xor_sync(0xffffffffu, l0, 2); l1 += __shfl_xor_sync(0xffffffffu, l1, 2);
    const float i0 = rcp(l0), i1 = rcp(l1);
    {
      const uint32_t t = tid_now();
      const uint32_t st_row = stg + ((t & 96) >> 1) * 128 + (t & 15) * 128;
      const uint32_t st_c = (t >> 4) & 1, st_x = t & 7;
#pragma unroll
      for (int j = 0; j < 16; j += 2) {
        const uint32_t ch = j + st_c;
        const uint32_t addr = st_row + (j >> 3) * hstride + (((ch & 7) ^ st_x) << 4);
        stsm_x4(addr, pack_bf16(accO[4 * j] * i0, accO[4 * j + 1] * i0), pack_bf16(accO[4 * j + 2] * i1, accO[4 * j + 3] * i1),
                pack_bf16(accO[4 * j + 4] * i0, accO[4 * j + 5] * i0), pack_bf16(accO[4 * j + 6] * i1, accO[4 * j + 7] * i1));
      }
    }
    fence_async_smem();
    mbar_arrive(bar + B_OFULL + 8 * wg);
    PROF_T(r * 3 + 2); PROF_G(62); PROF_T(63); PROF_D(42);
  }
}

constexpr uint32_t META_LIN = 0xEEEE4444u, META_SH = 0x44EEEE44u;
__device__ __forceinline__ void quad_to_sparse(uint32_t r0, uint32_t r1, uint32_t& a_lo, uint32_t& a_hi, const bool odd, const int src) {
  const uint32_t v1 = odd ? r1 : r0, v2 = odd ? r0 : r1;
  a_lo = __shfl_sync(0xffffffffu, v1, src);
  a_hi = __shfl_sync(0xffffffffu, v2, src ^ 1);
}

__device__ __forceinline__ uint32_t opaque_u32(uint32_t v) { uint32_t r; asm volatile("mov.b32 %0, %1;" : "=r"(r) : "r"(v)); return r; }

__device__ __forceinline__ void a_sparse(const uint32_t base, float (&acc)[64]) {
  constexpr int wg = 2;
  const uint32_t bar = base + BAR_OFF;
  const uint32_t a_full = bar + B_AFULL, a_empty = bar + B_AEMPTY;
  const uint32_t stg = base + A_STG_OFF;
  const float cs = SM_SCALE;
  int st = 0; uint32_t ph = 0, tph = 0;
  for (int r = 0;; r++) {
    mbar_wait(a_full + 8 * st, ph);
    if (wg_any(1 + wg, lds_s32(bar + B_ITEMQ + (r & 3) * 4) < 0 || r >= 64)) {
      mbar_wait(bar + B_OEMPTY + 8 * wg, (r - 1) & 1);
      mbar_arrive(bar + B_OFULL + 8 * wg);
      break;
    }
    PROF_T(r * 3); PROF_D(40);
    {
      uint32_t xa[8], xb[8];
      int prev = 0;
      const uint32_t metaq = opaque_u32(META_LIN);
      auto qstep = [&](uint32_t (&a)[8], auto first) {
        if (!decltype(first)::value) mbar_wait(a_full + 8 * st, ph);
        const uint32_t s = base + st * A_STAGE;
        const uint32_t t = tid_now();
        const uint32_t i = (t >> 2) & 7;
        const uint32_t xrow = s + (128 + ((t & 127) >> 2)) * 128 + (t & 1) * 8;
        const uint32_t c0 = (t >> 1) & 1;
#pragma unroll
        for (int q = 0; q < 4; q++) lds_v2(xrow + (((2 * q + c0) ^ i) << 4), a[2 * q], a[2 * q + 1]);
        const uint64_t db = make_desc(s + 20480, 8192, 1024);
        wg_fence();
        wgmma_sp<1, decltype(first)::value>(acc, a[0], a[1], a[2], a[3], db, metaq);
        wgmma_sp<1, false>(acc, a[4], a[5], a[6], a[7], db + 256, metaq);
        wg_commit();
        if (!decltype(first)::value) {
          wg_wait<1>();
          arrive_lane0(a_empty + 8 * prev);
        }
        prev = st;
        if (++st == A_NST) { st = 0; ph ^= 1; }
      };
      qstep(xa, BoolC<true>{});
#pragma unroll 1
      for (int c = 0; c < 4; c++) {
        qstep(xb, BoolC<false>{});
        qstep(xa, BoolC<false>{});
      }
      qstep(xb, BoolC<false>{});
      wg_wait<0>();
      fence_regs(acc);
      arrive_lane0(a_empty + 8 * prev);
    }
    PROF_T(r * 3 + 1); PROF_D(41);
    uint32_t qf[16];
    {
      const uint32_t t = tid_now();
      const bool odd = t & 1;
      const int src = (t & 28) | ((t & 1) << 1) | ((t >> 1) & 1);
#pragma unroll
      for (int hh = 0; hh < 8; hh++) {
        const uint32_t r0 = pack_bf16(acc[8 * hh] + acc[8 * hh + 2], acc[8 * hh + 1] + acc[8 * hh + 3]);
        const uint32_t r1 = pack_bf16(acc[8 * hh + 4] + acc[8 * hh + 6], acc[8 * hh + 5] + acc[8 * hh + 7]);
        quad_to_sparse(r0, r1, qf[2 * hh], qf[2 * hh + 1], odd, src);
      }
    }
    float m0 = -INFINITY, l0 = 0.f;
    float o[32];
#pragma unroll
    for (int j = 0; j < 32; j++) o[j] = 0.f;
    const uint32_t meta = opaque_u32(META_SH);
#pragma unroll 1
    for (int jb = 0; jb < 4; jb++) {
      PROF_D(jb * 8);
      mbar_wait(a_full + 8 * st, ph);
      PROF_D(jb * 8 + 1);
      {
        const uint32_t s = base + st * A_STAGE;
        const uint64_t dk = make_desc(s, 16, 1024);
        TOK_WAIT(2);
        PROF_D(jb * 8 + 2);
        wg_fence();
        wgmma_sp<0, true>(acc, qf[0], qf[1], qf[2], qf[3], dk, meta);
        wgmma_sp<0, false>(acc, qf[4], qf[5], qf[6], qf[7], dk + 4, meta);
        wgmma_sp<0, false>(acc, qf[8], qf[9], qf[10], qf[11], dk + 1024, meta);
        wgmma_sp<0, false>(acc, qf[12], qf[13], qf[14], qf[15], dk + 1028, meta);
        wg_commit();
        TOK_PASS(0);
        PROF_D(jb * 8 + 3);
        wg_wait<0>();
        PROF_D(jb * 8 + 4);
        arrive_lane0(a_empty + 8 * st);
        if (++st == A_NST) { st = 0; ph ^= 1; }
      }
      uint32_t p[16];
      float al0;
      {
        float sv[32];
#pragma unroll
        for (int j = 0; j < 16; j++) { sv[2 * j] = acc[4 * j] + acc[4 * j + 2]; sv[2 * j + 1] = acc[4 * j + 1] + acc[4 * j + 3]; }
        float x0 = fmaxf(sv[0], sv[1]);
#pragma unroll
        for (int j = 1; j < 16; j++) x0 = fmaxf(x0, fmaxf(sv[2 * j], sv[2 * j + 1]));
        x0 = fmaxf(x0, __shfl_xor_sync(0xffffffffu, x0, 1));
        x0 = fmaxf(x0, __shfl_xor_sync(0xffffffffu, x0, 2));
        x0 = fmaxf(m0, x0);
        al0 = ex2((m0 - x0) * cs);
        m0 = x0;
        const float c0 = -x0 * cs;
        float s0 = 0.f;
        const uint32_t t = tid_now();
        const bool odd = t & 1;
        const int src = (t & 28) | ((t & 1) << 1) | ((t >> 1) & 1);
#pragma unroll
        for (int hh = 0; hh < 8; hh++) {
          const float e0 = ex2(fmaf(sv[4 * hh], cs, c0)), e1 = ex2(fmaf(sv[4 * hh + 1], cs, c0));
          const float e2 = ex2(fmaf(sv[4 * hh + 2], cs, c0)), e3 = ex2(fmaf(sv[4 * hh + 3], cs, c0));
          s0 += (e0 + e1) + (e2 + e3);
          quad_to_sparse(pack_bf16(e0, e1), pack_bf16(e2, e3), p[2 * hh], p[2 * hh + 1], odd, src);
        }
        l0 = l0 * al0 + s0;
      }
      PROF_D(jb * 8 + 5);
      mbar_wait(a_full + 8 * st, ph);
      {
        const uint32_t s = base + st * A_STAGE;
        const uint64_t dv = make_desc(s, 16384, 1024);
        TOK_WAIT(2);
        PROF_D(jb * 8 + 6);
        wg_fence();
        wgmma_sp<1, true>(acc, p[0], p[1], p[2], p[3], dv, meta);
#pragma unroll
        for (int kk = 1; kk < 4; kk++) wgmma_sp<1, false>(acc, p[4 * kk], p[4 * kk + 1], p[4 * kk + 2], p[4 * kk + 3], dv + kk * 256, meta);
        wg_commit();
        TOK_PASS(1);
        PROF_D(jb * 8 + 7);
        wg_wait<0>();
        PROF_D(32 + jb);
        arrive_lane0(a_empty + 8 * st);
        if (++st == A_NST) { st = 0; ph ^= 1; }
      }
#pragma unroll
      for (int j = 0; j < 16; j++) {
        o[2 * j] = fmaf(o[2 * j], al0, acc[4 * j] + acc[4 * j + 2]);
        o[2 * j + 1] = fmaf(o[2 * j + 1], al0, acc[4 * j + 1] + acc[4 * j + 3]);
      }
    }
    l0 += __shfl_xor_sync(0xffffffffu, l0, 1);
    l0 += __shfl_xor_sync(0xffffffffu, l0, 2);
    const float i0 = rcp(l0);
    if (r > 0) mbar_wait(bar + B_OEMPTY + 8 * wg, (r - 1) & 1);
    {
      const uint32_t t = tid_now();
      const uint32_t st_row = stg + (((t & 96) >> 2) + (t & 7)) * 128;
      const uint32_t st_c = (t >> 3) & 3, st_x = t & 7;
#pragma unroll
      for (int j = 0; j < 16; j += 4) {
        const uint32_t addr = st_row + (j >> 3) * 4096 + ((((j + st_c) & 7) ^ st_x) << 4);
        stsm_x4(addr, pack_bf16(o[2 * j] * i0, o[2 * j + 1] * i0), pack_bf16(o[2 * j + 2] * i0, o[2 * j + 3] * i0),
                pack_bf16(o[2 * j + 4] * i0, o[2 * j + 5] * i0), pack_bf16(o[2 * j + 6] * i0, o[2 * j + 7] * i0));
      }
    }
    fence_async_smem();
    mbar_arrive(bar + B_OFULL + 8 * wg);
    PROF_T(r * 3 + 2); PROF_G(62); PROF_T(63); PROF_D(42);
  }
}

__device__ __forceinline__ void store_tile(const float (&acc)[64], __nv_bfloat16* __restrict__ dst  ) {
  const uint32_t t = tid_now();
  const bool b0 = t & 1, b1 = t & 2;
  uint4* p = reinterpret_cast<uint4*>(dst + (t & 3) * 8);
#pragma unroll
  for (int hr = 0; hr < 2; hr++) {
#pragma unroll
    for (int g = 0; g < 4; g++) {
      uint32_t a0 = pack_bf16(acc[16 * g + 2 * hr], acc[16 * g + 2 * hr + 1]);
      uint32_t a1 = pack_bf16(acc[16 * g + 4 + 2 * hr], acc[16 * g + 4 + 2 * hr + 1]);
      uint32_t a2 = pack_bf16(acc[16 * g + 8 + 2 * hr], acc[16 * g + 8 + 2 * hr + 1]);
      uint32_t a3 = pack_bf16(acc[16 * g + 12 + 2 * hr], acc[16 * g + 12 + 2 * hr + 1]);
      uint32_t x = b0 ? a0 : a1, y = b0 ? a2 : a3;
      x = __shfl_xor_sync(0xffffffffu, x, 1); y = __shfl_xor_sync(0xffffffffu, y, 1);
      if (b0) { a0 = x; a2 = y; } else { a1 = x; a3 = y; }
      x = b1 ? a0 : a2; y = b1 ? a1 : a3;
      x = __shfl_xor_sync(0xffffffffu, x, 2); y = __shfl_xor_sync(0xffffffffu, y, 2);
      if (b1) { a0 = x; a1 = y; } else { a2 = x; a3 = y; }
      p[hr * (8 * DM / 8) + g * 4] = make_uint4(a0, a1, a2, a3);
    }
  }
}

template <bool LAST>
__device__ __forceinline__ void p_role(const uint32_t base, const int wg, const int pidx, __nv_bfloat16* __restrict__ out,
                                       float (&accS)[64], float (&accO)[64]) {
  const uint32_t p_full = base + BAR_OFF + B_PFULL, p_empty = base + BAR_OFF + B_PEMPTY;
  const int g = pidx / 5, jt = pidx % 5;
  int st = 0; uint32_t ph = 0;
  for (int u = g; u < 16; u += 8) {
    int prev = 0;
    auto pstep = [&](auto first) {
      constexpr bool FIRST = decltype(first)::value;
      mbar_wait(p_full + 8 * st, ph);
      const uint32_t s = base + st * P_STAGE;
      const uint64_t da = make_desc(s + wg * 16384, 16, 1024);
      const uint64_t db = make_desc(s + 40960, 8192, 1024);
      wg_fence();
      wgmma_ss<1, FIRST>(accS, da, db);
#pragma unroll
      for (int kk = 1; kk < 4; kk++) wgmma_ss<1, false>(accS, da + kk * 2, db + kk * 128);
      if (!LAST) {
        wgmma_ss<1, FIRST>(accO, da + 512, db);
#pragma unroll
        for (int kk = 1; kk < 4; kk++) wgmma_ss<1, false>(accO, da + 512 + kk * 2, db + kk * 128);
      }
      wg_commit();
      if (!FIRST) {
        wg_wait<1>();
        arrive_lane0(p_empty + 8 * prev);
      }
      prev = st;
      if (++st == P_NST) { st = 0; ph ^= 1; }
    };
    pstep(BoolC<true>{});
#pragma unroll 1
    for (int c = 1; c < 64; c++) pstep(BoolC<false>{});
    wg_wait<0>();
    arrive_lane0(p_empty + 8 * prev);
    PROF_T(50 + (u >> 3) * 2);
    const uint32_t t = tid_now();
    const int row = u * 320 + wg * 128 + ((t & 96) >> 1) + ((t & 31) >> 2);
    __nv_bfloat16* o0 = out + (size_t)row * DM + jt * 128;
    store_tile(accS, o0);
    if (!LAST) store_tile(accO, o0 + 64 * DM);
    PROF_T(51 + (u >> 3) * 2); PROF_G(62); PROF_T(63);
  }
}

__global__ void __launch_bounds__(512, 1)
fused_kernel(const __grid_constant__ CUtensorMap tm_x, const __grid_constant__ CUtensorMap tm_wq,
             const __grid_constant__ CUtensorMap tm_k, const __grid_constant__ CUtensorMap tm_v,
             const __grid_constant__ CUtensorMap tm_ost, const __grid_constant__ CUtensorMap tm_old,
             const __grid_constant__ CUtensorMap tm_wo, __nv_bfloat16* __restrict__ out, const Sched sc) {
  extern __shared__ uint8_t smem_raw[];
  const uint32_t base = (smem_u32(smem_raw) + 1023) & ~1023u;
  const uint32_t bar = base + BAR_OFF;
  const uint32_t a_full = bar + B_AFULL, a_empty = bar + B_AEMPTY, p_full = bar + B_PFULL, p_empty = bar + B_PEMPTY;
  const uint32_t o_full = bar + B_OFULL, o_empty = bar + B_OEMPTY;
  const int tid = threadIdx.x, lane = tid & 31;
  const int warp = __shfl_sync(0xffffffffu, tid >> 5, 0), wg = warp >> 2;

  if (tid == 0) {
    for (int i = 0; i < A_NST; i++) { mbar_init(a_full + 8 * i, 1); mbar_init(a_empty + 8 * i, 12); }
    for (int i = 0; i < P_NST; i++) { mbar_init(p_full + 8 * i, 1); mbar_init(p_empty + 8 * i, 12); }
    for (int i = 0; i < 3; i++) { mbar_init(o_full + 8 * i, 128); mbar_init(o_empty + 8 * i, 1); mbar_init(bar + B_TOK + 8 * i, 4); }
    uint32_t t0;
    asm volatile("mov.u32 %0, %globaltimer_lo;" : "=r"(t0));
    sts_s32(bar + 248, (int)t0);
    asm volatile("fence.mbarrier_init.release.cluster;" ::: "memory");
  }
  __syncthreads();

  const int n_a = (int)gridDim.x - sc.n_p;
  const bool is_p = (int)blockIdx.x >= n_a;
  const int pidx = (int)blockIdx.x - n_a;

  if (wg == 3) {
    asm volatile("setmaxnreg.dec.sync.aligned.u32 32;");
    if (lane == 0) {
      if (warp == 12) {
        uint64_t pol;
        asm volatile("createpolicy.fractional.L2::evict_first.b64 %0, 1.0;" : "=l"(pol));
        int st = 0; uint32_t ph = 1;
        int it = blockIdx.x, r = 0;
        for (;; r++) {
          mbar_wait(a_empty + 8 * st, ph);
          sts_s32(bar + B_ITEMQ + (r & 3) * 4, it);
          if (it < 0) { mbar_arrive(a_full + 8 * st); break; }
          int b, h; item_bh(it, b, h);
          for (int c = 0; c < 10; c++) {
            if (c) mbar_wait(a_empty + 8 * st, ph);
            const uint32_t s = base + st * A_STAGE, fb = a_full + 8 * st;
            mbar_expect_tx(fb, 36864);
            tma_load_2d(s, &tm_x, c * 64, b * SQ, fb);
            tma_load_3d(s + 20480, &tm_wq, 0, c * 64, h * 2, fb);
            if (++st == A_NST) { st = 0; ph ^= 1; }
          }
          const int row0 = (b * NH + h) * SK;
          int nxt = -1;
          for (int j = 0; j < 8; j++) {
            mbar_wait(a_empty + 8 * st, ph);
            const uint32_t s = base + st * A_STAGE, fb = a_full + 8 * st;
            mbar_expect_tx(fb, 32768);
            tma_load_3d_hint(s, (j & 1) ? &tm_v : &tm_k, 0, row0 + (j >> 1) * 128, 0, fb, pol);
            if (++st == A_NST) { st = 0; ph ^= 1; }
            if (j == 6 && !is_p) {
              const unsigned int v = atomicAdd(&g_next, 1u);
              const unsigned int lim = NITEMS - gridDim.x;
              if (v < lim) nxt = (int)(v + gridDim.x);
              else if (v == lim + n_a - 1) atomicExch(&g_next, 0u);
            }
          }
          it = nxt;
        }
        if (is_p) {
          const unsigned int epoch = *(volatile unsigned int*)&g_epoch;
          __threadfence();
          if (atomicAdd(&g_done, 1u) == (unsigned)sc.n_p - 1u) {
            g_done = 0;
            __threadfence();
            *(volatile unsigned int*)&g_epoch = epoch + 1u;
          }
          for (int i = 1; i < A_NST; i++) {
            if (++st == A_NST) { st = 0; ph ^= 1; }
            mbar_wait(a_empty + 8 * st, ph);
          }
          for (int w = 0; w < 3; w++) mbar_wait(o_empty + 8 * w, (r - 1) & 1);
          const unsigned int target = 3u * (epoch + 1u);
          const int g = pidx / 5, jt = pidx % 5;
          st = 0; ph = 1;
          for (int u = g; u < 16; u += 8) {
            const int b0 = 2 * u;
            for (int h = 0; h < NH; h++) {
              for (int q = 0; q < 2; q++) {
                const unsigned int* fp = &g_flags[(b0 + q) * NH + h];
                unsigned int v;
                while (true) {
                  asm volatile("ld.acquire.gpu.global.u32 %0, [%1];" : "=r"(v) : "l"(fp) : "memory");
                  if (v == target) break;
                  __nanosleep(40);
                  if (deadline_passed()) break;
                }
              }
              asm volatile("fence.proxy.async.global;" ::: "memory");
              for (int hf = 0; hf < 2; hf++) {
                mbar_wait(p_empty + 8 * st, ph);
                const uint32_t s = base + st * P_STAGE, fb = p_full + 8 * st;
                mbar_expect_tx(fb, P_STAGE);
                tma_load_3d(s, &tm_old, 0, (b0 * NH + h) * SQ, hf, fb);
                tma_load_3d(s + 20480, &tm_old, 0, ((b0 + 1) * NH + h) * SQ, hf, fb);
                tma_load_3d(s + 40960, &tm_wo, 0, h * DH + hf * 64, jt * 2, fb);
                if (++st == P_NST) { st = 0; ph ^= 1; }
              }
            }
          }
        }
      } else {
        const int w = warp - 13;
        const uint32_t stg = base + A_STG_OFF + (w == 2 ? 0 : 8192 + w * 16384);
        const uint32_t hstride = (w == 2) ? 4096 : 8192;
        for (int r = 0;; r++) {
          mbar_wait(o_full + 8 * w, r & 1);
          const int it = lds_s32(bar + B_ITEMQ + (r & 3) * 4);
          if (it < 0 || r >= 64) break;
          int b, h; item_bh(it, b, h);
          const int slot = b * NH + h;
          const int row = slot * SQ + w * 64;
          for (int hf = 0; hf < 2; hf++) {
            tma_store_3d(&tm_ost, 0, row, hf, stg + hf * hstride);
            if (w < 2) tma_store_3d(&tm_ost, 0, row + 32, hf, stg + hf * hstride + 4096);
          }
          asm volatile("cp.async.bulk.commit_group;" ::: "memory");
          asm volatile("cp.async.bulk.wait_group.read 0;" ::: "memory");
          mbar_arrive(o_empty + 8 * w);
          asm volatile("cp.async.bulk.wait_group 0;" ::: "memory");
          asm volatile("fence.proxy.async.global;" ::: "memory");
          asm volatile("red.release.gpu.global.add.u32 [%0], 1;" ::"l"(&g_flags[slot]) : "memory");
        }
      }
    }
  } else if (wg == 2) {
    asm volatile("setmaxnreg.inc.sync.aligned.u32 160;");
    float accS[64], accO[64];
    PROF_CLR(); PROF_G(60); PROF_T(61);
    a_sparse(base, accS);
    if (is_p) p_role<true>(base, 2, pidx, out, accS, accO);
    PROF_DUMP();
  } else {
    asm volatile("setmaxnreg.inc.sync.aligned.u32 160;");
    float accS[64], accO[64];
    PROF_CLR(); PROF_G(60); PROF_T(61);
    a_dense(base, wg, sc.zero, accS, accO);
    if (is_p) p_role<false>(base, wg, pidx, out, accS, accO);
    PROF_DUMP();
  }
}

typedef CUresult (*EncodeFn)(CUtensorMap*, CUtensorMapDataType, cuuint32_t, void*, const cuuint64_t*, const cuuint64_t*,
                             const cuuint32_t*, const cuuint32_t*, CUtensorMapInterleave, CUtensorMapSwizzle,
                             CUtensorMapL2promotion, CUtensorMapFloatOOBfill);

void make_map(EncodeFn enc, CUtensorMap* m, const void* ptr, int rank, const cuuint64_t* dims, const cuuint64_t* strides,
              const cuuint32_t* box, CUtensorMapL2promotion promo) {
  cuuint32_t es[3] = {1, 1, 1};
  enc(m, CU_TENSOR_MAP_DATA_TYPE_BFLOAT16, rank, const_cast<void*>(ptr), dims, strides, box, es, CU_TENSOR_MAP_INTERLEAVE_NONE,
      CU_TENSOR_MAP_SWIZZLE_128B, promo, CU_TENSOR_MAP_FLOAT_OOB_FILL_NONE);
}

}

extern "C" void kernel_launch(void* const* d_in, const int* in_sizes, int n_in, void* d_out, int out_size) {
  (void)in_sizes; (void)n_in; (void)out_size;
  static EncodeFn enc = nullptr;
  static void* o_ptr = nullptr;
  if (!enc) {
    void* fn = nullptr;
    cudaDriverEntryPointQueryResult qr;
    cudaGetDriverEntryPoint("cuTensorMapEncodeTiled", &fn, cudaEnableDefault, &qr);
    enc = (EncodeFn)fn;
    cudaGetSymbolAddress(&o_ptr, g_O);
    cudaFuncSetAttribute(fused_kernel, cudaFuncAttributeMaxDynamicSharedMemorySize, SMEM_BYTES);
  }
  CUtensorMap tm_x, tm_wq, tm_k, tm_v, tm_ost, tm_old, tm_wo;
  {
    cuuint64_t d[2] = {DM, (cuuint64_t)NB * SQ}, s[1] = {DM * 2};
    cuuint32_t bx[2] = {64, SQ};
    make_map(enc, &tm_x, d_in[0], 2, d, s, bx, CU_TENSOR_MAP_L2_PROMOTION_L2_128B);
  }
  {
    cuuint64_t d[3] = {64, (cuuint64_t)NB * NH * SK, 2}, s[2] = {DH * 2, 128};
    cuuint32_t bx[3] = {64, 128, 2};
    make_map(enc, &tm_k, d_in[1], 3, d, s, bx, CU_TENSOR_MAP_L2_PROMOTION_L2_256B);
    make_map(enc, &tm_v, d_in[2], 3, d, s, bx, CU_TENSOR_MAP_L2_PROMOTION_L2_256B);
  }
  {
    cuuint64_t d[3] = {64, DM, (cuuint64_t)NH * 2}, s[2] = {(cuuint64_t)NH * DH * 2, 128};
    cuuint32_t bx[3] = {64, 64, 2};
    make_map(enc, &tm_wq, d_in[3], 3, d, s, bx, CU_TENSOR_MAP_L2_PROMOTION_L2_256B);
  }
  {
    cuuint64_t d[3] = {64, (cuuint64_t)NH * DH, DM / 64}, s[2] = {DM * 2, 128};
    cuuint32_t bx[3] = {64, 64, 2};
    make_map(enc, &tm_wo, d_in[4], 3, d, s, bx, CU_TENSOR_MAP_L2_PROMOTION_L2_256B);
  }
  {
    cuuint64_t d[3] = {64, (cuuint64_t)NITEMS * SQ, 2}, s[2] = {DH * 2, 128};
    cuuint32_t bs[3] = {64, 32, 1}, bl[3] = {64, SQ, 1};
    make_map(enc, &tm_ost, o_ptr, 3, d, s, bs, CU_TENSOR_MAP_L2_PROMOTION_NONE);
    make_map(enc, &tm_old, o_ptr, 3, d, s, bl, CU_TENSOR_MAP_L2_PROMOTION_L2_128B);
  }
  __nv_bfloat16* out = (__nv_bfloat16*)d_out;
  Sched sc{40, 0};
  fused_kernel<<<132, 512, SMEM_BYTES>>>(tm_x, tm_wq, tm_k, tm_v, tm_ost, tm_old, tm_wo, out, sc);
}
```

```cpp
#include <cuda_runtime.h>
#include <cuda_bf16.h>
#include <cuda.h>
#include <stdint.h>
#define FOLD

#define OROWS 32
#define STR_(x) #x
#define STR(x) STR_(x)
#define HINT_NS 20000
namespace {

constexpr int NB = 32, SQ = 160, DM = 640, NH = 32, SK = 512, DH = 128;
constexpr int NITEMS = NB * NH;

constexpr int Q_STAGE = 36864;
constexpr int QO_OFF = 5 * Q_STAGE;
constexpr int LP_OFF = QO_OFF + 40960;
constexpr int LI_OFF = LP_OFF + 5120;
constexpr int BAR_OFF = LI_OFF + 640;
constexpr int SMEM_BYTES = 232448;
constexpr int P_STAGE = 57344;
constexpr int P_NST = 4;
constexpr uint64_t TAB_K = 0x0929200929200400ull;
constexpr uint64_t TAB_V = 0x2920170D0400170Dull;
constexpr uint64_t TAB_P = 0x241B12241B12241Bull;

constexpr int B_QF = 0, B_QE = 80, B_KF = 160, B_VF = 224, B_KE = 288, B_PVD = 376  , B_PF = 440,
              B_TOK = 504, B_QRDY = 520, B_LP = 536, B_LI = 544, B_OF = 552, B_OE = 560, B_ITEMQ = 568, B_BAD = 584, B_T0 = 588,
              B_XF = 592  , B_FIN = B_PVD - 24, B_NRD = B_BAD, D_OF = 80  , D_OE = B_PVD - 16 - B_OE, B_PFULL = 0, B_PEMPTY = 80, B_END = 632;
constexpr int NJOBS = NITEMS / 2;

__device__ __nv_bfloat16 g_O[(size_t)NITEMS * SQ * DH];
__device__ unsigned int g_flags[NITEMS];
__device__ unsigned int g_epoch;
__device__ unsigned int g_done;
__device__ unsigned int g_next;
__device__ int g_redo[132 * 72];

#define PROF_T(idx)
#define PROF_D(idx)
#define PROF_G(idx)
#define PROF_P(idx)
#define PROF_X(row, idx)
#define PROF_DUMP()
#define PROF_CLR()
__device__ __forceinline__ uint32_t smem_u32(const void* p) { return (uint32_t)__cvta_generic_to_shared(p); }
__device__ __forceinline__ uint64_t make_desc(uint32_t addr) {
  return (uint64_t)((addr & 0x3FFFF) >> 4) | ((uint64_t)1 << 16) | ((uint64_t)(1024 >> 4) << 32) | ((uint64_t)1 << 62);
}
__device__ __forceinline__ void mbar_init(uint32_t bar, int cnt) {
  asm volatile("mbarrier.init.shared::cta.b64 [%0], %1;" ::"r"(bar), "r"(cnt));
}
__device__ __forceinline__ void mbar_expect_tx(uint32_t bar, uint32_t bytes) {
  asm volatile("mbarrier.arrive.expect_tx.shared::cta.b64 _, [%0], %1;" ::"r"(bar), "r"(bytes) : "memory");
}
__device__ __forceinline__ void mbar_arrive(uint32_t bar) {
  asm volatile("mbarrier.arrive.shared::cta.b64 _, [%0];" ::"r"(bar) : "memory");
}
__device__ __forceinline__ bool mbar_try(uint32_t bar, uint32_t parity) {
  uint32_t done;
  asm volatile("{\n.reg .pred p;\nmbarrier.try_wait.parity.shared::cta.b64 p, [%1], %2;\nselp.u32 %0, 1, 0, p;\n}"
               : "=r"(done) : "r"(bar), "r"(parity) : "memory");
  return done != 0;
}
__device__ __forceinline__ bool deadline_passed() {
  extern __shared__ __align__(1024) uint8_t smem_raw[];
  const uint32_t a = smem_u32(smem_raw) + BAR_OFF + B_T0;
  uint32_t t0, t1;
  asm volatile("ld.shared.u32 %0, [%1];" : "=r"(t0) : "r"(a) : "memory");
  asm volatile("mov.u32 %0, %globaltimer_lo;" : "=r"(t1));
  return (t1 - t0) > 500000000u;
}
#define TRY_LONG(P, A, B) "mbarrier.try_wait.parity.shared::cta.b64 " P ", [" A "], " B ", " STR(HINT_NS) ";\n"
#define WAIT_LOOP(L, A, B, T) L ":\n" TRY_LONG("p", A, B) "@p bra.uni " L "D;\n" \
  "ld.shared.u32 t0, [" T "];\nmov.u32 t1, %globaltimer_lo;\nsub.u32 t1, t1, t0;\nsetp.lt.u32 p, t1, 500000000;\n@p bra.uni " L ";\n" L "D:\n"
__device__ __forceinline__ uint32_t t0_addr() {
  extern __shared__ __align__(1024) uint8_t smem_raw[];
  return smem_u32(smem_raw) + BAR_OFF + B_T0;
}
__device__ __forceinline__ void mbar_wait(uint32_t bar, uint32_t parity) {
  asm volatile("{\n.reg .pred p;\n.reg .u32 t0, t1;\n"
               "mbarrier.try_wait.parity.shared::cta.b64 p, [%0], %1;\n@p bra.uni WD;\n"
               WAIT_LOOP("W", "%0", "%1", "%2") "}"
               ::"r"(bar), "r"(parity), "r"(t0_addr()) : "memory");
}
__device__ __forceinline__ void mbar_wait2(uint32_t b0, uint32_t p0, uint32_t b1, uint32_t p1) {
  asm volatile("{\n.reg .pred p, q;\n.reg .u32 t0, t1;\n"
               "mbarrier.try_wait.parity.shared::cta.b64 p, [%0], %1;\nmbarrier.try_wait.parity.shared::cta.b64 q, [%2], %3;\n"
               "and.pred p, p, q;\n@p bra.uni VD;\n"
               WAIT_LOOP("W", "%0", "%1", "%4") WAIT_LOOP("V", "%2", "%3", "%4") "}"
               ::"r"(b0), "r"(p0), "r"(b1), "r"(p1), "r"(t0_addr()) : "memory");
}
__device__ __forceinline__ void tma_load_2d(uint32_t dst, const CUtensorMap* m, int c0, int c1, uint32_t bar) {
  asm volatile("cp.async.bulk.tensor.2d.shared::cluster.global.mbarrier::complete_tx::bytes [%0], [%1, {%3, %4}], [%2];"
               ::"r"(dst), "l"(m), "r"(bar), "r"(c0), "r"(c1) : "memory");
}
__device__ __forceinline__ void tma_load_3d(uint32_t dst, const CUtensorMap* m, int c0, int c1, int c2, uint32_t bar) {
  asm volatile("cp.async.bulk.tensor.3d.shared::cluster.global.mbarrier::complete_tx::bytes [%0], [%1, {%3, %4, %5}], [%2];"
               ::"r"(dst), "l"(m), "r"(bar), "r"(c0), "r"(c1), "r"(c2) : "memory");
}
__device__ __forceinline__ void tma_load_3d_hint(uint32_t dst, const CUtensorMap* m, int c0, int c1, int c2, uint32_t bar, uint64_t pol) {
  asm volatile("cp.async.bulk.tensor.3d.shared::cluster.global.mbarrier::complete_tx::bytes.L2::cache_hint [%0], [%1, {%3, %4, %5}], [%2], %6;"
               ::"r"(dst), "l"(m), "r"(bar), "r"(c0), "r"(c1), "r"(c2), "l"(pol) : "memory");
}
__device__ __forceinline__ void tma_store_3d(const CUtensorMap* m, int c0, int c1, int c2, uint32_t src) {
  asm volatile("cp.async.bulk.tensor.3d.global.shared::cta.bulk_group [%0, {%2, %3, %4}], [%1];"
               ::"l"(m), "r"(src), "r"(c0), "r"(c1), "r"(c2) : "memory");
}
__device__ __forceinline__ void tma_store_2d(const CUtensorMap* m, int c0, int c1, uint32_t src) {
  asm volatile("cp.async.bulk.tensor.2d.global.shared::cta.bulk_group [%0, {%2, %3}], [%1];"
               ::"l"(m), "r"(src), "r"(c0), "r"(c1) : "memory");
}
#define ELECT_BEGIN "{\n.reg .pred p;\nelect.sync _|p, 0xffffffff;\n"
__device__ __forceinline__ void e_expect(uint32_t bar, uint32_t bytes) {
  asm volatile(ELECT_BEGIN "@p mbarrier.arrive.expect_tx.shared::cta.b64 _, [%0], %1;\n}" ::"r"(bar), "r"(bytes) : "memory");
}
__device__ __forceinline__ void e_arrive2(uint32_t bar, uint32_t rbar) {
  asm volatile(ELECT_BEGIN "@p mbarrier.arrive.shared::cta.b64 _, [%0];\n@p mbarrier.arrive.shared::cluster.b64 _, [%1];\n}"
               ::"r"(bar), "r"(rbar) : "memory");
}
__device__ __forceinline__ void e_load_3d(uint32_t dst, const CUtensorMap* m, int c0, int c1, int c2, uint32_t bar) {
  asm volatile(ELECT_BEGIN "@p cp.async.bulk.tensor.3d.shared::cluster.global.mbarrier::complete_tx::bytes [%0], [%1, {%3, %4, %5}], [%2];\n}"
               ::"r"(dst), "l"(m), "r"(bar), "r"(c0), "r"(c1), "r"(c2) : "memory");
}
__device__ __forceinline__ void e_load_3d_hint(uint32_t dst, const CUtensorMap* m, int c0, int c1, int c2, uint32_t bar, uint64_t pol) {
  asm volatile(ELECT_BEGIN "@p cp.async.bulk.tensor.3d.shared::cluster.global.mbarrier::complete_tx::bytes.L2::cache_hint [%0], [%1, {%3, %4, %5}], [%2], %6;\n}"
               ::"r"(dst), "l"(m), "r"(bar), "r"(c0), "r"(c1), "r"(c2), "l"(pol) : "memory");
}
__device__ __forceinline__ void e_load_2d_mc(uint32_t dst, const CUtensorMap* m, int c0, int c1, uint32_t bar) {
  asm volatile(ELECT_BEGIN "@p cp.async.bulk.tensor.2d.shared::cluster.global.mbarrier::complete_tx::bytes.multicast::cluster [%0], [%1, {%3, %4}], [%2], %5;\n}"
               ::"r"(dst), "l"(m), "r"(bar), "r"(c0), "r"(c1), "h"((uint16_t)3) : "memory");
}
__device__ __forceinline__ void e_load_3d_mc(uint32_t dst, const CUtensorMap* m, int c0, int c1, int c2, uint32_t bar) {
  asm volatile(ELECT_BEGIN "@p cp.async.bulk.tensor.3d.shared::cluster.global.mbarrier::complete_tx::bytes.multicast::cluster [%0], [%1, {%3, %4, %5}], [%2], %6;\n}"
               ::"r"(dst), "l"(m), "r"(bar), "r"(c0), "r"(c1), "r"(c2), "h"((uint16_t)3) : "memory");
}
__device__ __forceinline__ uint32_t mapa(uint32_t a, uint32_t rank) {
  uint32_t r; asm volatile("mapa.shared::cluster.u32 %0, %1, %2;" : "=r"(r) : "r"(a), "r"(rank)); return r;
}
__device__ __forceinline__ void cluster_sync() {
  asm volatile("barrier.cluster.arrive.relaxed.aligned;\nbarrier.cluster.wait.aligned;" ::: "memory");
}
__device__ __forceinline__ unsigned int read_epoch(const unsigned int readers) {
  unsigned int e = 0;
  if ((threadIdx.x & 31) == 0) {
    e = *(volatile unsigned int*)&g_epoch;
    __threadfence();
    if (atomicAdd(&g_done, 1u) == readers - 1u) {
      g_done = 0;
      __threadfence();
      *(volatile unsigned int*)&g_epoch = e + 1u;
    }
  }
  return __shfl_sync(0xffffffffu, e, 0);
}
__device__ __forceinline__ void wait_flag(const unsigned int* fp, const unsigned int target) {
  while (true) {
    unsigned int v;
    asm volatile("ld.acquire.gpu.global.u32 %0, [%1];" : "=r"(v) : "l"(fp) : "memory");
    if (v == target) break;
    __nanosleep(40);
    if (deadline_passed()) break;
  }
}
__device__ __forceinline__ void wg_fence() { asm volatile("wgmma.fence.sync.aligned;" ::: "memory"); }
__device__ __forceinline__ void wg_commit() { asm volatile("wgmma.commit_group.sync.aligned;" ::: "memory"); }
template <int N> __device__ __forceinline__ void wg_wait() { asm volatile("wgmma.wait_group.sync.aligned %0;" ::"n"(N) : "memory"); }
__device__ __forceinline__ void fence_async_smem() { asm volatile("fence.proxy.async.shared::cta;" ::: "memory"); }
__device__ __forceinline__ void named_bar(int id, int n) { asm volatile("bar.sync %0, %1;" ::"r"(id), "r"(n) : "memory"); }
__device__ __forceinline__ uint32_t tid_now() { uint32_t t; asm volatile("mov.u32 %0, %tid.x;" : "=r"(t)); return t; }
__device__ __forceinline__ void arrive_lane0(uint32_t bar) {
  asm volatile("{\n.reg .pred p;\nelect.sync _|p, 0xffffffff;\n@p mbarrier.arrive.shared::cta.b64 _, [%0];\n}" ::"r"(bar) : "memory");
}
__device__ __forceinline__ float rcp(float x) { float y; asm("rcp.approx.ftz.f32 %0, %1;" : "=f"(y) : "f"(x)); return y; }
__device__ __forceinline__ float ex2(float x) { float y; asm("ex2.approx.ftz.f32 %0, %1;" : "=f"(y) : "f"(x)); return y; }
__device__ __forceinline__ uint32_t pack_bf16(float lo, float hi) {
  uint32_t r; asm("cvt.rn.bf16x2.f32 %0, %1, %2;" : "=r"(r) : "f"(hi), "f"(lo)); return r;
}
__device__ __forceinline__ void stsm_x4_t(uint32_t addr, uint32_t r0, uint32_t r1, uint32_t r2, uint32_t r3) {
  asm volatile("stmatrix.sync.aligned.m8n8.x4.trans.shared.b16 [%0], {%1, %2, %3, %4};" ::"r"(addr), "r"(r0), "r"(r1), "r"(r2), "r"(r3) : "memory");
}
__device__ __forceinline__ int lds_s32(uint32_t a) { int v; asm volatile("ld.shared.s32 %0, [%1];" : "=r"(v) : "r"(a) : "memory"); return v; }
__device__ __forceinline__ void sts_s32(uint32_t a, int v) { asm volatile("st.shared.s32 [%0], %1;" ::"r"(a), "r"(v) : "memory"); }
__device__ __forceinline__ float lds_f32(uint32_t a) { float v; asm volatile("ld.shared.f32 %0, [%1];" : "=f"(v) : "r"(a) : "memory"); return v; }
__device__ __forceinline__ void sts_f32(uint32_t a, float v) { asm volatile("st.shared.f32 [%0], %1;" ::"r"(a), "f"(v) : "memory"); }
__device__ __forceinline__ void lds_f32x2(uint32_t a, float& x, float& y) {
  asm volatile("ld.shared.v2.f32 {%0, %1}, [%2];" : "=f"(x), "=f"(y) : "r"(a) : "memory");
}

#define ACC_STR                                                                        \
  "{%0, %1, %2, %3, %4, %5, %6, %7, %8, %9, %10, %11, %12, %13, %14, %15, "            \
  "%16, %17, %18, %19, %20, %21, %22, %23, %24, %25, %26, %27, %28, %29, %30, %31, "   \
  "%32, %33, %34, %35, %36, %37, %38, %39, %40, %41, %42, %43, %44, %45, %46, %47, "   \
  "%48, %49, %50, %51, %52, %53, %54, %55, %56, %57, %58, %59, %60, %61, %62, %63, "   \
  "%64, %65, %66, %67, %68, %69, %70, %71, %72, %73, %74, %75, %76, %77, %78, %79}, "
#define ACC8(C, d, o) C(d[o]), C(d[o + 1]), C(d[o + 2]), C(d[o + 3]), C(d[o + 4]), C(d[o + 5]), C(d[o + 6]), C(d[o + 7])
#define ACC_OPS(C, d) ACC8(C, d, 0), ACC8(C, d, 8), ACC8(C, d, 16), ACC8(C, d, 24), ACC8(C, d, 32), ACC8(C, d, 40), ACC8(C, d, 48), \
                      ACC8(C, d, 56), ACC8(C, d, 64), ACC8(C, d, 72)

#define DESC_STR "{\n.reg .b32 x, y, h;\n.reg .b64 a, b;\n.reg .pred p;\nadd.u32 x, %80, %81;\nadd.u32 y, %82, %83;\nmov.b32 h, 0x40000040;\n" \
                 "mov.b64 a, {x, h};\nmov.b64 b, {y, h};\n"
template <int TA, bool INIT, int IA, int IB>
__device__ __forceinline__ void wgmma(float (&d)[80], uint32_t a, uint32_t b) {
  if constexpr (INIT) {
    asm volatile(DESC_STR "wgmma.mma_async.sync.aligned.m64n160k16.f32.bf16.bf16 " ACC_STR "a, b, 0, 1, 1, %84, 0;\n}"
                 : ACC_OPS("=f", d) : "r"(a), "n"(IA), "r"(b), "n"(IB), "n"(TA));
  } else {
    asm volatile(DESC_STR "wgmma.mma_async.sync.aligned.m64n160k16.f32.bf16.bf16 " ACC_STR "a, b, 1, 1, 1, %84, 0;\n}"
                 : ACC_OPS("+f", d) : "r"(a), "n"(IA), "r"(b), "n"(IB), "n"(TA));
  }
}
__device__ __forceinline__ void wgmma_t_p(float (&d)[80], uint32_t a, uint32_t b, uint32_t acc) {
  asm volatile(DESC_STR "setp.ne.u32 p, %84, 0;\n"
               "wgmma.mma_async.sync.aligned.m64n160k16.f32.bf16.bf16 " ACC_STR "a, b, p, 1, 1, 1, 0;\n}"
               : ACC_OPS("+f", d) : "r"(a), "n"(0), "r"(b), "n"(0), "r"(acc));
}
template <bool INIT, int IA, int IB>
__device__ __forceinline__ void mma_t4(float (&d)[80], uint32_t a, uint32_t b) {
  wgmma<1, INIT, IA, IB>(d, a, b);
  wgmma<1, false, IA + 128, IB + 2>(d, a, b);
  wgmma<1, false, IA + 256, IB + 4>(d, a, b);
  wgmma<1, false, IA + 384, IB + 6>(d, a, b);
}
template <bool INIT, int IA, int IB>
__device__ __forceinline__ void mma_n4(float (&d)[80], uint32_t a, uint32_t b) {
  wgmma<0, INIT, IA, IB>(d, a, b);
  wgmma<0, false, IA + 2, IB + 2>(d, a, b);
  wgmma<0, false, IA + 4, IB + 4>(d, a, b);
  wgmma<0, false, IA + 6, IB + 6>(d, a, b);
}
template <int V> struct IntC { static constexpr int value = V; };
__device__ __forceinline__ bool wg_any(int id, bool v) {
  uint32_t r;
  asm volatile("{\n.reg .pred p, q;\nsetp.ne.u32 q, %2, 0;\nbarrier.cta.red.or.pred p, %1, 128, q;\nselp.u32 %0, 1, 0, p;\n}"
               : "=r"(r) : "r"(id), "r"((uint32_t)v) : "memory");
  return __shfl_sync(0xffffffffu, r, 0) != 0;
}
__device__ __forceinline__ void job_bh(int j, int& b, int& h) {
  b = ((j >> 8) << 4) + (j & 15);
  h = ((j & 255) >> 4) * 2 + (int)(blockIdx.x & 1);
}
struct Sched {
  int n_p;
  int k_first;
  int zero;
  int stag_a, stag_p;
  const __nv_bfloat16* kp;
  const __nv_bfloat16* vp;
};
template <int N> __device__ __forceinline__ void fence_regs(float (&d)[N]) {
#pragma unroll
  for (int i = 0; i < N; i++) asm volatile("" : "+f"(d[i])::"memory");
}
template <bool V> struct BoolC { static constexpr bool value = V; };
constexpr float SM_SCALE = 0.08838834764831845f * 1.4426950408889634f;
__device__ __forceinline__ uint32_t tab(uint64_t t, int i) { return ((uint32_t)(t >> (8 * i)) & 0xffu) << 12; }

__device__ __forceinline__ uint32_t stsm_lane_off() {
  const uint32_t t = tid_now();
  const uint32_t i = t & 7, m = (t >> 3) & 3, w = (t >> 5) & 3;
  return ((m >> 1) * 8 + i) * 128 + (((2 * w + (m & 1)) ^ i) << 4);
}

__device__ __forceinline__ void slow_item(__nv_bfloat16* qo, const __nv_bfloat16* __restrict__ kp, const __nv_bfloat16* __restrict__ vp) {
  const int lane = threadIdx.x & 31, warp = threadIdx.x >> 5;
  for (int q = warp * 20; q < warp * 20 + 20; q++) {
    float s[16];
#pragma unroll
    for (int j = 0; j < 16; j++) s[j] = 0.f;
    for (int d = 0; d < 16; d++) {
      const uint4 qq = __ldcg(reinterpret_cast<const uint4*>(qo + q * DH + d * 8));
      const uint32_t qv[4] = {qq.x, qq.y, qq.z, qq.w};
#pragma unroll
      for (int j = 0; j < 16; j++) {
        const uint4 kv = *reinterpret_cast<const uint4*>(kp + (size_t)(lane + 32 * j) * DH + d * 8);
        const uint32_t kk[4] = {kv.x, kv.y, kv.z, kv.w};
#pragma unroll
        for (int e = 0; e < 4; e++) {
          s[j] = fmaf(__uint_as_float(qv[e] << 16), __uint_as_float(kk[e] << 16), s[j]);
          s[j] = fmaf(__uint_as_float(qv[e] & 0xffff0000u), __uint_as_float(kk[e] & 0xffff0000u), s[j]);
        }
      }
    }
    float m = s[0];
#pragma unroll
    for (int j = 1; j < 16; j++) m = fmaxf(m, s[j]);
    for (int o = 16; o > 0; o >>= 1) m = fmaxf(m, __shfl_xor_sync(0xffffffffu, m, o));
    float l = 0.f;
#pragma unroll
    for (int j = 0; j < 16; j++) {
      s[j] = ex2(s[j] - m);
      l += s[j];
    }
    for (int o = 16; o > 0; o >>= 1) l += __shfl_xor_sync(0xffffffffu, l, o);
    float o0 = 0.f, o1 = 0.f, o2 = 0.f, o3 = 0.f;
#pragma unroll
    for (int j = 0; j < 16; j++) {
#pragma unroll 4
      for (int src = 0; src < 32; src++) {
        const float p = __shfl_sync(0xffffffffu, s[j], src);
        const uint2 vv = *reinterpret_cast<const uint2*>(vp + (size_t)(src + 32 * j) * DH + lane * 4);
        o0 = fmaf(p, __uint_as_float(vv.x << 16), o0); o1 = fmaf(p, __uint_as_float(vv.x & 0xffff0000u), o1);
        o2 = fmaf(p, __uint_as_float(vv.y << 16), o2); o3 = fmaf(p, __uint_as_float(vv.y & 0xffff0000u), o3);
      }
    }
    const float il = 1.f / l;
    __syncwarp();
    *reinterpret_cast<uint2*>(qo + q * DH + lane * 4) = make_uint2(pack_bf16(o0 * il, o1 * il), pack_bf16(o2 * il, o3 * il));
  }
}

#define EA 2
#define EB 5
#define EC 8
#define ECE 3
#define OPEND 1
#define EC0 3
#define QE0 3
#define QE1 3
#define SPLIT0 2
#define SPLIT1 8
#define SPLIT2 14
__device__ __forceinline__ void sched_boundary(const int zero) {
  for (int i = zero; i > 0; i--) asm volatile("nanosleep.u32 0;");
}
__device__ __forceinline__ uint64_t desc_lo(uint32_t lo) { return (uint64_t)lo | ((uint64_t)0x40000040u << 32); }
__device__ __forceinline__ uint32_t tab8(uint64_t t, int i) { return ((uint32_t)(t >> (8 * i)) & 0xffu) << 8; }
__device__ __forceinline__ void a_role(const uint32_t base, const int wg, const Sched& sc, float (&accS)[80], float (&accO)[80]) {
  const uint32_t bar = base + BAR_OFF;
  const uint32_t dbase = (base >> 4) | 0x10000u;
  const uint32_t dbw = dbase + wg * 512;
  const float cs = SM_SCALE;
  uint32_t tph = 0;
  auto qstep = [&](auto cc, const uint32_t ph) {
    constexpr int c = decltype(cc)::value, so = (c % 5) * (Q_STAGE >> 4);
    mbar_wait(bar + B_QF + 8 * c, ph);
    wg_fence();
    mma_t4<c == 0, so + 1280, so>(accS, dbw, dbase);
    wg_commit();
  };
  auto pv = [&](const int t) {
    const uint32_t da = dbw + tab8(TAB_V, t), db = dbase + tab8(TAB_P, t);
    wg_fence();
    wgmma_t_p(accO, da, db, t);
    wgmma<1, false, 128, 2>(accO, da, db);
    wgmma<1, false, 256, 4>(accO, da, db);
    wgmma<1, false, 384, 6>(accO, da, db);
    wg_commit();
  };
  auto p_done = [&](const int t) {
    fence_async_smem();
    __syncwarp();
    arrive_lane0(bar + B_PF + 8 * t);
  };
  float l[40];
#pragma unroll
  for (int j = 0; j < 80; j++) accO[j] = 0.f;
  if (wg == 1) arrive_lane0(bar + B_TOK);
  qstep(IntC<0>{}, 0);
#pragma unroll 1
  for (int c = 1; c < 10; c++) {
    const uint32_t so = (c >= 5 ? c - 5 : c) * (Q_STAGE >> 4);
    mbar_wait(bar + B_QF + 8 * c, 0);
    wg_fence();
    mma_t4<false, 1280, 0>(accS, dbw + so, dbase + so);
    wg_commit();
    wg_wait<1>();
    arrive_lane0(bar + B_QE + 8 * (c - 1));
  }
  for (int r = 0;; r++) {
    const uint32_t ph = r & 1;
    const bool last = wg_any(1 + wg, lds_s32(bar + B_ITEMQ + ((r + 1) & 3) * 4) < 0 || r >= 64);
    if (r > 0) mbar_wait(bar + B_OE + wg * D_OE, ph ^ 1);
    const uint32_t lane_off = stsm_lane_off();
    wg_wait<0>();
    fence_regs(accS);
    arrive_lane0(bar + B_QE + 72);
    PROF_T(r * 3 + 1); PROF_D(40); PROF_D(41);
    {
      const uint32_t a = base + QO_OFF + wg * 20480 + lane_off;
      const float qs = cs;
#pragma unroll
      for (int j = 0; j < 20; j += 2)
        stsm_x4_t(a + j * 1024, pack_bf16(accS[4 * j] * qs, accS[4 * j + 1] * qs), pack_bf16(accS[4 * j + 2] * qs, accS[4 * j + 3] * qs),
                  pack_bf16(accS[4 * j + 4] * qs, accS[4 * j + 5] * qs), pack_bf16(accS[4 * j + 6] * qs, accS[4 * j + 7] * qs));
    }
    fence_async_smem();
    __syncwarp();
    arrive_lane0(bar + B_QRDY + 8 * wg);
    mbar_wait(bar + B_QRDY, ph);
    auto tile = [&](const int T, auto firstc) {
      constexpr bool FIRST = decltype(firstc)::value;
      const uint32_t dk = dbase + tab8(TAB_K, T);
      PROF_D(T * 4);
      mbar_wait2(bar + B_KF + 8 * T, ph, bar + B_TOK + 8 * wg, tph); tph ^= 1;
      PROF_D(T * 4 + 1);
      wg_fence();
      mma_n4<true, 0, (QO_OFF >> 4)>(accS, dk, dbase);
      if constexpr (FIRST) {
        wg_commit();
        mbar_wait(bar + B_QRDY + 8, ph);
        wg_fence();
      }
      mma_n4<false, 512, (QO_OFF >> 4) + 1280>(accS, dk, dbase);
      wg_commit();
      const uint32_t a = base + (tab8(TAB_P, T) << 4) + lane_off;
      if constexpr (FIRST) {
        arrive_lane0(bar + B_TOK + 8 * (wg ^ 1));
        wg_wait<0>();
        fence_regs(accS);
      } else {
        p_done(T - 2);
        if (T >= 3) pv(T - 3); else { wg_fence(); wg_commit(); }
        mbar_wait2(bar + B_VF + 8 * (T - 2), ph, bar + B_PF + 8 * (T - 2), ph);
        wg_wait<1>();
        fence_regs(accS);
        pv(T - 2);
        arrive_lane0(bar + B_TOK + 8 * (wg ^ 1));
      }
      PROF_D(T * 4 + 2);
      arrive_lane0(bar + B_KE + 8 * T);
      uint32_t p[40];
      auto sm = [&](const int j) {
        const float e0 = ex2(accS[4 * j]), e1 = ex2(accS[4 * j + 1]), e2 = ex2(accS[4 * j + 2]), e3 = ex2(accS[4 * j + 3]);
        if constexpr (FIRST) { l[2 * j] = e0 + e2; l[2 * j + 1] = e1 + e3; }
        else { l[2 * j] += e0; l[2 * j + 1] += e1; l[2 * j] += e2; l[2 * j + 1] += e3; }
        p[2 * j] = pack_bf16(e0, e1); p[2 * j + 1] = pack_bf16(e2, e3);
      };
      if constexpr (FIRST) {
#pragma unroll
        for (int j = 0; j < 20; j++) {
          sm(j);
          if (j & 1) stsm_x4_t(a + (j - 1) * 1024, p[2 * j - 2], p[2 * j - 1], p[2 * j], p[2 * j + 1]);
        }
      } else {
#pragma unroll
        for (int j = 0; j < SPLIT0; j++) sm(j);
        sched_boundary(sc.zero);
#pragma unroll
        for (int j = SPLIT0; j < SPLIT1; j++) sm(j);
        sched_boundary(sc.zero);
        wg_wait<1>();
        arrive_lane0(bar + B_PVD + 8 * (T - 3));
#pragma unroll
        for (int j = SPLIT1; j < SPLIT2; j++) sm(j);
        mbar_wait(bar + B_PVD + 8 * (T - 3), ph);
        wg_wait<0>();
        arrive_lane0(bar + B_PVD + 8 * (T - 2));
#pragma unroll
        for (int j = SPLIT2; j < 20; j++) {
          sm(j);
          constexpr int per = (10 + (20 - SPLIT2) - 1) / (20 - SPLIT2);
#pragma unroll
          for (int e = 0; e < per; e++) {
            const int q = (j - SPLIT2) * per + e;
            if (q < 10 && 2 * q + 1 <= j && j < 19) stsm_x4_t(a + q * 2048, p[4 * q], p[4 * q + 1], p[4 * q + 2], p[4 * q + 3]);
          }
        }
#pragma unroll
        for (int q = 0; q < 10; q++) {
          constexpr int per = (10 + (20 - SPLIT2) - 1) / (20 - SPLIT2);
          const int j = SPLIT2 + q / per;
          if (!(2 * q + 1 <= j && j < 19)) stsm_x4_t(a + q * 2048, p[4 * q], p[4 * q + 1], p[4 * q + 2], p[4 * q + 3]);
        }
      }
      PROF_D(T * 4 + 3);
    };
    tile(wg, BoolC<true>{});
#pragma unroll 1
    for (int T = wg + 2; T < 8; T += 2) tile(T, BoolC<false>{});
    mbar_wait(bar + B_TOK + 8 * wg, tph); tph ^= 1;
    pv(5 + wg);
    p_done(6 + wg);
    mbar_wait2(bar + B_VF + 8 * (6 + wg), ph, bar + B_PF + 8 * (6 + wg), ph);
    pv(6 + wg);
    arrive_lane0(bar + B_TOK + 8 * (wg ^ 1));
    PROF_D(32);
    sched_boundary(sc.zero);
    {
      const bool b4 = tid_now() & 16;
#pragma unroll
      for (int j = 0; j < 20; j++) {
        const float snd = b4 ? l[j] : l[j + 20], kp = b4 ? l[j + 20] : l[j];
        l[j] = kp + __shfl_xor_sync(0xffffffffu, snd, 16);
      }
    }
    sched_boundary(sc.zero);
    wg_wait<1>();
    arrive_lane0(bar + B_PVD + 8 * (5 + wg));
    auto bf2 = [&]() {
      const uint32_t t = tid_now();
      const bool b4 = t & 16, b3 = t & 8, b2 = t & 4;
#pragma unroll
      for (int j = 0; j < 10; j++) {
        const float snd = b3 ? l[j] : l[j + 10], kp = b3 ? l[j + 10] : l[j];
        l[j] = kp + __shfl_xor_sync(0xffffffffu, snd, 8);
      }
#pragma unroll
      for (int j = 0; j < 5; j++) {
        const float snd = b2 ? l[j] : l[j + 5], kp = b2 ? l[j + 5] : l[j];
        l[j] = kp + __shfl_xor_sync(0xffffffffu, snd, 4);
      }
      const uint32_t i0 = (b4 ? 20 : 0) + (b3 ? 10 : 0) + (b2 ? 5 : 0);
      const uint32_t a = base + LP_OFF + (t >> 5) * 640 + i0 * 16 + (t & 3) * 4;
#pragma unroll
      for (int j = 0; j < 5; j++) sts_f32(a + j * 16, l[j]);
      __syncwarp();
      arrive_lane0(bar + B_LP);
      PROF_D(33);
    };
    auto pv7 = [&]() {
      if (wg == 0) {
        mbar_wait2(bar + B_VF + 56, ph, bar + B_PF + 56, ph);
        pv(7);
      }
    };
    auto epi_begin = [&]() -> bool {
      mbar_wait(bar + B_LI, ph);
      const bool bad = lds_s32(bar + B_BAD) != 0;
      const uint32_t li = base + LI_OFF + (tid_now() & 3) * 8;
#pragma unroll
      for (int j = 0; j < 20; j++) lds_f32x2(li + j * 32, l[2 * j], l[2 * j + 1]);
      return bad;
    };
    auto epi = [&](const int q0, const int q1) {
      const uint32_t a = base + QO_OFF + wg * 20480 + lane_off;
#pragma unroll
      for (int j = 2 * q0; j < 2 * q1; j += 2) {
        const float i0 = l[2 * j], i1 = l[2 * j + 1], i2 = l[2 * j + 2], i3 = l[2 * j + 3];
        stsm_x4_t(a + j * 1024, pack_bf16(accO[4 * j] * i0, accO[4 * j + 1] * i1), pack_bf16(accO[4 * j + 2] * i0, accO[4 * j + 3] * i1),
                  pack_bf16(accO[4 * j + 4] * i2, accO[4 * j + 5] * i3), pack_bf16(accO[4 * j + 6] * i2, accO[4 * j + 7] * i3));
      }
    };
    auto epi_end = [&]() {
      fence_async_smem();
      __syncwarp();
      arrive_lane0(bar + B_OF + wg * D_OF);
      PROF_T(r * 3 + 2); PROF_G(62); PROF_T(63); PROF_D(42);
    };
    if (last) {
      bf2();
      pv7();
      wg_wait<0>();
      fence_regs(accO);
      if (!epi_begin()) epi(0, 10);
      epi_end();
      break;
    }
    PROF_T(r * 3 + 3);
    qstep(IntC<0>{}, ph ^ 1);
    sched_boundary(sc.zero);
    bf2();
    wg_wait<1>();
    arrive_lane0(bar + B_PVD + 8 * (6 + wg));
    qstep(IntC<1>{}, ph ^ 1);
    PROF_D(34);
    pv7();
    PROF_D(35);
    qstep(IntC<2>{}, ph ^ 1);
    wg_wait<1>();
    fence_regs(accO);
    if (wg == 0) arrive_lane0(bar + B_PVD + 56);
    arrive_lane0(bar + B_QE);
    arrive_lane0(bar + B_QE + 8);
    PROF_D(36);
    bool bad = false;
    auto step = [&](auto cc) {
      constexpr int c = decltype(cc)::value;
      qstep(cc, ph ^ 1);
      PROF_D((wg ^ 1) * 4 + ((c - 3) >> 2) * 8 + ((c - 3) & 3));
      if (c == EC0) bad = epi_begin();
      if (c == EC0 && !bad) epi(0, EA);
      if (c == EC0 + 1 && !bad) epi(EA, EB);
      if (c == EC0 + 2 && !bad) epi(EB, EC);
      if (c == EC0 + 3 && !bad) epi(EC, 10);
      wg_wait<1>();
      arrive_lane0(bar + B_QE + 8 * (c - 1));
      if (c == EC0 + ECE) epi_end();
    };
    step(IntC<3>{}); step(IntC<4>{}); step(IntC<5>{}); step(IntC<6>{}); step(IntC<7>{}); step(IntC<8>{}); step(IntC<9>{});
  }
}

__device__ __forceinline__ void p_role(const uint32_t base, const int wg, const int g, const int jt, const uint32_t ph0, const CUtensorMap* tm_out,
                                       float (&accS)[80], float (&accO)[80]) {
  const uint32_t p_full = base + BAR_OFF + B_PFULL, p_empty = base + BAR_OFF + B_PEMPTY;
  int st = 0; uint32_t ph = ph0;
  for (int u = g; u < 16; u += 8) {
    int prev = 0;
    auto pstep = [&](auto first) {
      constexpr bool FIRST = decltype(first)::value;
      mbar_wait(p_full + 8 * st, ph);
      const uint32_t s = base + st * P_STAGE;
      const uint32_t db = (s >> 4) | 0x10000u, da = db + wg * 512;
      wg_fence();
      mma_t4<FIRST, 2560, 0>(accS, da, db);
      mma_t4<FIRST, 2560, 1280>(accO, da, db);
      wg_commit();
      if (!FIRST) {
        wg_wait<1>();
        arrive_lane0(p_empty + 8 * prev);
      }
      prev = st;
      if (++st == P_NST) { st = 0; ph ^= 1; }
    };
    pstep(BoolC<true>{});
#pragma unroll 1
    for (int c = 1; c < 64; c++) pstep(BoolC<false>{});
    wg_wait<0>();
    fence_regs(accS); fence_regs(accO);
    arrive_lane0(p_empty + 8 * prev);
    PROF_T(50 + (u >> 3) * 2);
    const int s0 = st, s1 = st + 1;
    mbar_wait(p_full + 8 * s0, ph);
    mbar_wait(p_full + 8 * s1, ph);
    const uint32_t stg = base + (wg ? s1 : s0) * P_STAGE;
    {
      const uint32_t a = stg + stsm_lane_off();
#pragma unroll
      for (int j = 0; j < 20; j += 2) {
        stsm_x4_t(a + j * 1024, pack_bf16(accS[4 * j], accS[4 * j + 1]), pack_bf16(accS[4 * j + 2], accS[4 * j + 3]),
                  pack_bf16(accS[4 * j + 4], accS[4 * j + 5]), pack_bf16(accS[4 * j + 6], accS[4 * j + 7]));
        stsm_x4_t(a + 20480 + j * 1024, pack_bf16(accO[4 * j], accO[4 * j + 1]), pack_bf16(accO[4 * j + 2], accO[4 * j + 3]),
                  pack_bf16(accO[4 * j + 4], accO[4 * j + 5]), pack_bf16(accO[4 * j + 6], accO[4 * j + 7]));
      }
    }
    fence_async_smem();
    named_bar(1 + wg, 128);
    if ((tid_now() & 127) == 0) {
      tma_store_2d(tm_out, jt * 128 + wg * 64, u * 320, stg);
      tma_store_2d(tm_out, jt * 128 + wg * 64, u * 320 + 160, stg + 20480);
      asm volatile("cp.async.bulk.commit_group;" ::: "memory");
      asm volatile("cp.async.bulk.wait_group.read 0;" ::: "memory");
    }
    named_bar(1 + wg, 128);
    arrive_lane0(p_empty + 8 * s0);
    arrive_lane0(p_empty + 8 * s1);
    st = (st + 2) & 3;
    if (st < 2) ph ^= 1;
    PROF_T(51 + (u >> 3) * 2); PROF_G(62); PROF_T(63);
  }
  asm volatile("cp.async.bulk.wait_group 0;" ::: "memory");
}

__global__ void __cluster_dims__(2, 1, 1) __launch_bounds__(384, 1)
fused_kernel(const __grid_constant__ CUtensorMap tm_x, const __grid_constant__ CUtensorMap tm_wq,
             const __grid_constant__ CUtensorMap tm_k, const __grid_constant__ CUtensorMap tm_v,
             const __grid_constant__ CUtensorMap tm_o, const __grid_constant__ CUtensorMap tm_wo,
             const __grid_constant__ CUtensorMap tm_out, const __grid_constant__ CUtensorMap tm_os, const Sched sc) {
  extern __shared__ __align__(1024) uint8_t smem_raw[];
  const uint32_t base = smem_u32(smem_raw);
  const uint32_t bar = base + BAR_OFF;
  const int tid = threadIdx.x, lane = tid & 31;
  const int warp = __shfl_sync(0xffffffffu, tid >> 5, 0), wg = warp >> 2;
  const int cl = blockIdx.x >> 1, rank = blockIdx.x & 1, ncl = gridDim.x >> 1;

  if (tid == 32) {
    asm volatile("prefetch.tensormap [%0];" ::"l"(&tm_x) : "memory");
    asm volatile("prefetch.tensormap [%0];" ::"l"(&tm_wq) : "memory");
    asm volatile("prefetch.tensormap [%0];" ::"l"(&tm_k) : "memory");
    asm volatile("prefetch.tensormap [%0];" ::"l"(&tm_v) : "memory");
  }
  if (tid == 0) {
    for (int i = 0; i < 10; i++) { mbar_init(bar + B_QF + 8 * i, 1); mbar_init(bar + B_QE + 8 * i, 8); }
    for (int i = 0; i < 8; i++) {
      mbar_init(bar + B_KF + 8 * i, 1); mbar_init(bar + B_VF + 8 * i, 1); mbar_init(bar + B_KE + 8 * i, 4);
      mbar_init(bar + B_PVD + 8 * i, 8); mbar_init(bar + B_PF + 8 * i, 4);
    }
    mbar_init(bar + B_PVD - 8, 4); mbar_init(bar + B_FIN, 1);
    mbar_init(bar + B_TOK, 4); mbar_init(bar + B_TOK + 8, 4); mbar_init(bar + B_QRDY, 4); mbar_init(bar + B_QRDY + 8, 4);
    mbar_init(bar + B_LP, 8); mbar_init(bar + B_LI, 1); mbar_init(bar + B_OF, 4); mbar_init(bar + B_OE, 1);
    mbar_init(bar + B_OF + D_OF, 4); mbar_init(bar + (B_OE + D_OE), 1);
    for (int i = 0; i < 5; i++) mbar_init(bar + B_XF + 8 * i, 2);
    uint32_t t0;
    asm volatile("mov.u32 %0, %globaltimer_lo;" : "=r"(t0));
    sts_s32(bar + B_T0, (int)t0);
    sts_s32(bar + B_ITEMQ, cl);
    asm volatile("fence.mbarrier_init.release.cluster;" ::: "memory");
  }
  __syncthreads();
  cluster_sync();

  const int n_a = ncl - sc.n_p;
  const bool is_p = cl >= n_a;
  const int pidx = cl - n_a;
  const int pk = pidx % 5;
  const bool w_share = pk == 4;
  const int pg = (pidx / 5) * 2 + (w_share ? rank : (pk >> 1));
  const int pj = w_share ? 4 : (pk & 1) * 2 + rank;

  if (wg == 2) {
    asm volatile("setmaxnreg.dec.sync.aligned.u32 40;");
    const uint32_t rbar = mapa(bar, rank ^ 1);
    if (warp == 8) {
      uint64_t pol;
      asm volatile("createpolicy.fractional.L2::evict_first.b64 %0, 1.0;" : "=l"(pol));
      {
        const uint32_t delay = is_p ? pidx * sc.stag_p : cl * sc.stag_a;
        uint32_t t0, t1;
        asm volatile("mov.u32 %0, %clock;" : "=r"(t0));
        do { __nanosleep(100); asm volatile("mov.u32 %0, %clock;" : "=r"(t1)); } while (t1 - t0 < delay);
      }
      int r = 0;
      for (; r <= 64; r++) {
        const uint32_t ph = r & 1;
        const int it = __shfl_sync(0xffffffffu, lds_s32(bar + B_ITEMQ + (r & 3) * 4), 0);
        if (it < 0) break;
        int b, h; job_bh(it, b, h);
#pragma unroll
        for (int c = 0; c < 10; c++) {
          if (c >= 5) mbar_wait(bar + B_QE + 8 * (c - 5), ph);
          else if (r > 0) {
            mbar_wait(bar + B_PVD + 8 * (c + 3), ph ^ 1);
            if (c == 1) mbar_wait(bar + B_KE + 56, ph ^ 1);
          }
          const uint32_t s = base + (c % 5) * Q_STAGE, fb = bar + B_QF + 8 * c;
          PROF_P(c);
          e_arrive2(bar + B_XF + 8 * (c % 5), rbar + B_XF + 8 * (c % 5));
          e_expect(fb, c == 9 ? Q_STAGE + 4 : Q_STAGE);
          e_load_3d(s + 20480, &tm_wq, 0, c * 64, h * 2, fb);
        }
        const int row0 = (b * NH + h) * SK;
        constexpr int SEQ_T[16] = {0, 1, 8, 4, 9, 2, 3, 10, 11, 5, 6, 12, 7, 13, 14, 15};
        constexpr int SEQ_W[16] = {B_QE + 40, -1, B_QE + 48, -1, B_QE + 56, B_QE + 64, B_QE + 72, B_KE, B_KE + 8, B_KE + 16, B_KE + 24,
                                   B_PVD, B_KE + 32, B_PVD + 8, B_KE + 40, B_KE + 48};
#pragma unroll
        for (int j = 0; j < 16; j++) {
          const int id = SEQ_T[j], t = id & 7;
          if (SEQ_W[j] >= 0) mbar_wait(bar + SEQ_W[j], ph);
          const uint32_t fb = bar + B_KF + 8 * id;
          PROF_P(10 + j);
          e_expect(fb, 16384);
          e_load_3d_hint(base + tab(id >= 8 ? TAB_V : TAB_K, t), id >= 8 ? &tm_v : &tm_k, 0, row0 + t * 64, 0, fb, pol);
        }
      }
      if (is_p) {
        const unsigned int target = read_epoch(4u * sc.n_p) + 1u;
        mbar_wait(bar + (B_OE + D_OE), (r - 1) & 1);
        const uint32_t p_full = bar + B_PFULL, p_empty = bar + B_PEMPTY;
        int st = 0; uint32_t ph = (r - 1) & 1;
        for (int u = pg; u < 16; u += 8) {
          const int b0 = 2 * u;
          for (int h = 0; h < NH; h++) {
            if (w_share) {
              wait_flag(&g_flags[b0 * NH + h], target);
              wait_flag(&g_flags[(b0 + 1) * NH + h], target);
              asm volatile("fence.proxy.async.global;" ::: "memory");
            }
#pragma unroll
            for (int hf = 0; hf < 2; hf++) {
              mbar_wait(p_empty + 8 * st, ph);
              const uint32_t s = base + st * P_STAGE, fb = p_full + 8 * st;
              e_arrive2(bar + B_XF + 8 * st, rbar + B_XF + 8 * st);
              e_expect(fb, P_STAGE);
              if (w_share) {
                e_load_3d(s, &tm_o, 0, (b0 * NH + h) * SQ, hf, fb);
                e_load_3d(s + 20480, &tm_o, 0, ((b0 + 1) * NH + h) * SQ, hf, fb);
              } else {
                e_load_3d(s + 40960, &tm_wo, 0, h * DH + hf * 64, pj * 2, fb);
                e_load_3d(s + 49152, &tm_wo, 0, h * DH + hf * 64, pj * 2 + 1, fb);
              }
              if (++st == P_NST) { st = 0; ph ^= 1; }
            }
          }
          for (int e = 0; e < 2; e++) {
            mbar_wait(p_empty + 8 * st, ph);
            arrive_lane0(p_full + 8 * st);
            if (++st == P_NST) { st = 0; ph ^= 1; }
          }
        }
      }
    } else if (warp == 11) {
      for (int r = 0; r <= 64; r++) {
        const int it = __shfl_sync(0xffffffffu, lds_s32(bar + B_ITEMQ + (r & 3) * 4), 0);
        if (it < 0) break;
        int b, h; job_bh(it, b, h);
        unsigned int v = 0;
#pragma unroll
        for (int c = 0; c < 10; c++) {
          mbar_wait(bar + B_XF + 8 * (c % 5), c / 5);
          PROF_P(30 + c);
          e_load_2d_mc(base + (c % 5) * Q_STAGE + rank * 10240, &tm_x, c * 64, b * SQ + rank * 80, bar + B_QF + 8 * c);
          if (c == 0 && rank == 0 && !is_p && lane == 0) v = atomicAdd(&g_next, 1u);
          if (c == 5 && rank == 0 && lane == 0) {
            int nxt = -1;
            const unsigned int off = ncl + sc.n_p * (sc.k_first - 1);
            const unsigned int lim = NJOBS - off;
            if (!is_p) {
              if (v < lim) nxt = (int)(v + off);
              else if (v == lim + n_a - 1) atomicExch(&g_next, 0u);
            } else if (r + 1 < sc.k_first) nxt = ncl + r * sc.n_p + pidx;
            const uint32_t q = B_ITEMQ + ((r + 1) & 3) * 4, lb = mapa(bar, 0);
            asm volatile("st.async.shared::cluster.mbarrier::complete_tx::bytes.s32 [%0], %1, [%2];" ::"r"(lb + q), "r"(nxt), "r"(lb + B_QF + 72) : "memory");
            asm volatile("st.async.shared::cluster.mbarrier::complete_tx::bytes.s32 [%0], %1, [%2];" ::"r"(rbar + q), "r"(nxt), "r"(rbar + B_QF + 72) : "memory");
          }
          __syncwarp();
        }
        mbar_wait(bar + B_QF + 72, r & 1);
      }
      if (is_p) {
        const unsigned int target = read_epoch(4u * sc.n_p) + 1u;
        int st = 0; uint32_t xph = 0;
        for (int u = pg; u < 16; u += 8) {
          const int bb = 2 * u + rank;
          for (int h = 0; h < NH; h++) {
            if (!w_share) {
              wait_flag(&g_flags[bb * NH + h], target);
              PROF_X(3, h + (u >> 3) * 32);
              asm volatile("fence.proxy.async.global;" ::: "memory");
            }
#pragma unroll
            for (int hf = 0; hf < 2; hf++) {
              mbar_wait(bar + B_XF + 8 * st, (xph >> st) & 1);
              xph ^= 1u << st;
              const uint32_t s = base + st * P_STAGE, fb = bar + B_PFULL + 8 * st;
              if (w_share) e_load_3d_mc(s + 40960 + rank * 8192, &tm_wo, 0, h * DH + hf * 64, pj * 2 + rank, fb);
              else e_load_3d_mc(s + rank * 20480, &tm_o, 0, (bb * NH + h) * SQ, hf, fb);
              st = (st + 1) & 3;
            }
          }
          st = (st + 2) & 3;
        }
      }
    } else if (warp == 9) {
      if (lane == 0) {
        int nrd = 0;
        for (int r = 0; r <= 64; r++) {
          mbar_wait(bar + B_OF, r & 1);
          int b, h; job_bh(lds_s32(bar + B_ITEMQ + (r & 3) * 4), b, h);
          const int slot = b * NH + h;
          const int nx = lds_s32(bar + B_ITEMQ + ((r + 1) & 3) * 4);
          const int bad = lds_s32(bar + B_BAD);
          for (int hf = 0; hf < 2; hf++) {
            if (hf) mbar_wait(bar + B_OF + D_OF, r & 1);
            PROF_X(2, hf);
            for (int i = 0; i < 160 / OROWS; i++) {
              tma_store_3d(&tm_os, 0, slot * SQ + i * OROWS, hf, base + QO_OFF + hf * 20480 + i * OROWS * 128);
              asm volatile("cp.async.bulk.commit_group;" ::: "memory");
              if (nx >= 0) asm volatile("cp.async.bulk.wait_group.read %0;" ::"n"(OPEND) : "memory");
            }
            asm volatile("cp.async.bulk.wait_group.read 0;" ::: "memory");
            mbar_arrive(bar + B_OE + hf * D_OE);
          }
          asm volatile("cp.async.bulk.wait_group 0;" ::: "memory");
          asm volatile("fence.proxy.async.global;" ::: "memory");
          if (bad) g_redo[blockIdx.x * 72 + nrd++] = slot;
          else asm volatile("red.release.gpu.global.add.u32 [%0], 1;" ::"l"(&g_flags[slot]) : "memory");
          PROF_X(2, 2);
          if (nx < 0) break;
        }
        sts_s32(bar + B_NRD, nrd);
        __threadfence();
        mbar_arrive(bar + B_FIN);
      }
    } else {
      for (int r = 0; r <= 64; r++) {
        mbar_wait(bar + B_LP, r & 1);
        float s[5] = {0.f, 0.f, 0.f, 0.f, 0.f};
#pragma unroll
        for (int w = 0; w < 8; w++) {
          float v0, v1, v2, v3, v4;
          asm volatile("ld.shared.v4.f32 {%0, %1, %2, %3}, [%4];" : "=f"(v0), "=f"(v1), "=f"(v2), "=f"(v3) : "r"(base + LP_OFF + w * 640 + lane * 16));
          asm volatile("ld.shared.f32 %0, [%1];" : "=f"(v4) : "r"(base + LP_OFF + w * 640 + 512 + lane * 4));
          s[0] += v0; s[1] += v1; s[2] += v2; s[3] += v3; s[4] += v4;
        }
        bool bad = false;
#pragma unroll
        for (int k = 0; k < 5; k++) {
          bad |= !(s[k] >= 5.4210109e-20f && s[k] <= 1.2089258e24f);
          const int i = k < 4 ? lane : 32 + (lane >> 2), q = k < 4 ? k : (lane & 3);
          sts_f32(base + LI_OFF + (8 * (i >> 1) + 2 * q + (i & 1)) * 4, rcp(s[k]));
        }
        bad = __any_sync(0xffffffffu, bad);
        const int nx = lds_s32(bar + B_ITEMQ + ((r + 1) & 3) * 4);
        if (lane == 0) sts_s32(bar + B_BAD, bad);
        __syncwarp();
        if (lane == 0) mbar_arrive(bar + B_LI);
        if (__shfl_sync(0xffffffffu, nx, 0) < 0) break;
      }
    }
    __syncwarp();
  } else {
    asm volatile("setmaxnreg.inc.sync.aligned.u32 232;");
    float accS[80], accO[80];
    PROF_CLR(); PROF_G(60); PROF_T(61);
    a_role(base, wg, sc, accS, accO);
    mbar_wait(bar + B_FIN, 0);
    const int nrd = min(lds_s32(bar + B_NRD), 65);
    for (int i = 0; i < nrd; i++) {
      const int slot = __ldcg(&g_redo[blockIdx.x * 72 + i]) & (NITEMS - 1);
      slow_item(g_O + (size_t)slot * SQ * DH, sc.kp + (size_t)slot * SK * DH, sc.vp + (size_t)slot * SK * DH);
      asm volatile("fence.proxy.async.global;" ::: "memory");
      __syncwarp();
      if (lane == 0) {
        __threadfence();
        if ((atomicAdd(&g_redo[blockIdx.x * 72 + i], NITEMS) >> 10) == 7) {
          __threadfence();
          asm volatile("red.release.gpu.global.add.u32 [%0], 1;" ::"l"(&g_flags[slot]) : "memory");
        }
      }
      __syncwarp();
    }
    if (is_p) p_role(base, wg, pg, pj, sc.k_first & 1, &tm_out, accS, accO);
    PROF_DUMP();
  }
  cluster_sync();
}

typedef CUresult (*EncodeFn)(CUtensorMap*, CUtensorMapDataType, cuuint32_t, void*, const cuuint64_t*, const cuuint64_t*,
                             const cuuint32_t*, const cuuint32_t*, CUtensorMapInterleave, CUtensorMapSwizzle,
                             CUtensorMapL2promotion, CUtensorMapFloatOOBfill);

void make_map(EncodeFn enc, CUtensorMap* m, const void* ptr, int rank, const cuuint64_t* dims, const cuuint64_t* strides,
              const cuuint32_t* box, CUtensorMapL2promotion promo) {
  cuuint32_t es[3] = {1, 1, 1};
  enc(m, CU_TENSOR_MAP_DATA_TYPE_BFLOAT16, rank, const_cast<void*>(ptr), dims, strides, box, es, CU_TENSOR_MAP_INTERLEAVE_NONE,
      CU_TENSOR_MAP_SWIZZLE_128B, promo, CU_TENSOR_MAP_FLOAT_OOB_FILL_NONE);
}

}

#define KFIRST 2

extern "C" void kernel_launch(void* const* d_in, const int* in_sizes, int n_in, void* d_out, int out_size) {
  (void)in_sizes; (void)n_in; (void)out_size;
  static EncodeFn enc = nullptr;
  static void* o_ptr = nullptr;
  if (!enc) {
    void* fn = nullptr;
    cudaDriverEntryPointQueryResult qr;
    cudaGetDriverEntryPoint("cuTensorMapEncodeTiled", &fn, cudaEnableDefault, &qr);
    enc = (EncodeFn)fn;
    cudaGetSymbolAddress(&o_ptr, g_O);
    cudaFuncSetAttribute(fused_kernel, cudaFuncAttributeMaxDynamicSharedMemorySize, SMEM_BYTES);
  }
  CUtensorMap tm_x, tm_wq, tm_k, tm_v, tm_o, tm_wo, tm_out, tm_os;
  {
    cuuint64_t d[2] = {DM, (cuuint64_t)NB * SQ}, s[1] = {DM * 2};
    cuuint32_t bx[2] = {64, SQ}, bh[2] = {64, SQ / 2};
    make_map(enc, &tm_x, d_in[0], 2, d, s, bh, CU_TENSOR_MAP_L2_PROMOTION_L2_128B);
    make_map(enc, &tm_out, d_out, 2, d, s, bx, CU_TENSOR_MAP_L2_PROMOTION_NONE);
  }
  {
    cuuint64_t d[3] = {64, (cuuint64_t)NB * NH * SK, 2}, s[2] = {DH * 2, 128};
    cuuint32_t bx[3] = {64, 64, 2};
    make_map(enc, &tm_k, d_in[1], 3, d, s, bx, (CUtensorMapL2promotion)(2));
    make_map(enc, &tm_v, d_in[2], 3, d, s, bx, (CUtensorMapL2promotion)(2));
  }
  {
    cuuint64_t d[3] = {64, DM, (cuuint64_t)NH * 2}, s[2] = {(cuuint64_t)NH * DH * 2, 128};
    cuuint32_t bx[3] = {64, 64, 2};
    make_map(enc, &tm_wq, d_in[3], 3, d, s, bx, (CUtensorMapL2promotion)(3));
  }
  {
    cuuint64_t d[3] = {64, (cuuint64_t)NH * DH, DM / 64}, s[2] = {DM * 2, 128};
    cuuint32_t bx[3] = {64, 64, 1};
    make_map(enc, &tm_wo, d_in[4], 3, d, s, bx, (CUtensorMapL2promotion)(3));
  }
  {
    cuuint64_t d[3] = {64, (cuuint64_t)NITEMS * SQ, 2}, s[2] = {DH * 2, 128};
    cuuint32_t bl[3] = {64, SQ, 1};
    make_map(enc, &tm_o, o_ptr, 3, d, s, bl, CU_TENSOR_MAP_L2_PROMOTION_L2_128B);
    cuuint32_t bs[3] = {64, OROWS, 1};
    make_map(enc, &tm_os, o_ptr, 3, d, s, bs, CU_TENSOR_MAP_L2_PROMOTION_NONE);
  }
  Sched sc{20, KFIRST, 0, 400, 0, (const __nv_bfloat16*)d_in[1], (const __nv_bfloat16*)d_in[2]};
  fused_kernel<<<132, 384, SMEM_BYTES>>>(tm_x, tm_wq, tm_k, tm_v, tm_o, tm_wo, tm_out, tm_os, sc);
}
```

```cpp
#include <cuda_runtime.h>
#include <cuda_bf16.h>
#include <cuda.h>
#include <stdint.h>

#define N1 20
#define LOOKC 0
#define TAKEC 4
#define FASTLAST 1
#define STR_(x) #x
#define STR(x) STR_(x)
#define HINT_NS 20000
namespace {

constexpr int NB = 32, SQ = 160, DM = 640, NH = 32, SK = 512, DH = 128;
constexpr int NITEMS = NB * NH;

constexpr int Q_STAGE = 36864;
constexpr int QO_OFF = 5 * Q_STAGE;
constexpr int LP_OFF = QO_OFF + 40960;
constexpr int LI_OFF = LP_OFF + 5120;
constexpr int BAR_OFF = LI_OFF + 640;
constexpr int SMEM_BYTES = 232448;
constexpr int P_STAGE = 57344;
constexpr int P_NST = 4;
constexpr uint64_t TAB_K = 0x0D04291709002924ull;
constexpr uint64_t TAB_V = 0x2920170900200D04ull;
constexpr uint64_t TAB_P = 0x241B12241B12241Bull;

constexpr int B_QF = 0, B_QE = 80, B_KF = 160, B_VF = 224, B_KE = 288, B_PVD = 376  , B_PF = 440,
              B_TOK = 504, B_QRDY = 520, B_LP = 536, B_LI = 544, B_OF = 552, B_OE = 560, B_ITEMQ = 568, B_BAD = 584, B_T0 = 588,
              B_XF = 592  , B_XF5 = 640, B_FIN = B_PVD - 24, B_NRD = B_BAD, D_OF = 80  , D_OE = B_PVD - 16 - B_OE, B_PFULL = 0, B_PEMPTY = 80,
              B_HB = 648, B_AD = 656, B_NB = 664, B_DUM = 668, B_DEC = 672, B_HQ = 680  , B_STG = 696  , B_NOP = 704, B_ZF = 712, B_SIDE = 720, B_TGT = 724;
constexpr int C_OUT = 2048, C_RED = 4096, C_NOP = 8192, HC_OPEN = 512;
__host__ __device__ constexpr int q_reg(int c) { return c == 0 ? 0 : c == 1 ? 5 : c < 6 ? c - 1 : c - 6; }
__host__ __device__ constexpr int xf_bar(int c) { return c == 1 ? B_XF5 : B_XF + 8 * q_reg(c); }
__host__ __device__ constexpr int bar_cnt(int o) {
  return o < B_QE ? 1 : o < B_KF ? 8 : o < B_KE ? 1 : o < B_FIN ? 4 : o < B_PVD - 8 ? 1 : o < B_PVD ? 4 : o < B_PF ? 8 : o < B_LP ? 4
       : o == B_LP ? 8 : o == B_LI ? 1 : o == B_OF ? 4 : o == B_OE ? 1 : o < B_XF ? 0 : o < B_OF + D_OF ? 2 : o == B_OF + D_OF ? 4
       : o == B_XF5 ? 2 : o == B_HB ? 1 : o == B_AD || o == B_NOP ? 8 : o == B_ZF ? 2 : 0;
}
constexpr int NJOBS = NITEMS / 2;

constexpr size_t O_BYTES = (size_t)NITEMS * 65536;
__device__ uint8_t g_O[O_BYTES + (4 << 20)];
__device__ unsigned int g_pol[32];
__host__ __device__ constexpr int o_piece(int slot, int hf) { return ((slot & ~1) + hf) * 8 + ((slot ^ hf) & 1); }
constexpr uint32_t SIDE1_SLOTS = 0x66996699u;
__device__ unsigned int g_flags[NITEMS];
__device__ unsigned int g_busy[NITEMS / 32];
__device__ unsigned int g_cons[NITEMS];
__device__ unsigned int g_hc[10 * 32];
__device__ unsigned int g_next[64];
__device__ unsigned int g_fast[NJOBS];
__device__ unsigned int g_fin;
__device__ int g_redo[132 * 72];

#define PROF_T(idx)
#define PROF_D(idx)
#define PROF_G(idx)
#define PROF_P(idx)
#define PROF_X(row, idx)
#define PROF_DUMP()
#define PROF_CLR()
__device__ __forceinline__ uint32_t smem_u32(const void* p) { return (uint32_t)__cvta_generic_to_shared(p); }
__device__ __forceinline__ void mbar_init(uint32_t bar, int cnt) {
  asm volatile("mbarrier.init.shared::cta.b64 [%0], %1;" ::"r"(bar), "r"(cnt));
}
__device__ __forceinline__ void mbar_arrive(uint32_t bar) {
  asm volatile("mbarrier.arrive.shared::cta.b64 _, [%0];" ::"r"(bar) : "memory");
}
__device__ __forceinline__ bool mbar_try(uint32_t bar, uint32_t parity) {
  uint32_t done;
  asm volatile("{\n.reg .pred p;\nmbarrier.test_wait.parity.shared::cta.b64 p, [%1], %2;\nselp.u32 %0, 1, 0, p;\n}"
               : "=r"(done) : "r"(bar), "r"(parity) : "memory");
  return done != 0;
}
__device__ __forceinline__ bool deadline_passed() {
  extern __shared__ __align__(1024) uint8_t smem_raw[];
  const uint32_t a = smem_u32(smem_raw) + BAR_OFF + B_T0;
  uint32_t t0, t1;
  asm volatile("ld.shared.u32 %0, [%1];" : "=r"(t0) : "r"(a) : "memory");
  asm volatile("mov.u32 %0, %globaltimer_lo;" : "=r"(t1));
  return (t1 - t0) > 500000000u;
}
#define TRY_LONG(P, A, B) "mbarrier.try_wait.parity.shared::cta.b64 " P ", [" A "], " B ", " STR(HINT_NS) ";\n"
#define WAIT_LOOP(L, A, B, T) L ":\n" TRY_LONG("p", A, B) "@p bra.uni " L "D;\n" \
  "ld.shared.u32 t0, [" T "];\nmov.u32 t1, %globaltimer_lo;\nsub.u32 t1, t1, t0;\nsetp.lt.u32 p, t1, 500000000;\n@p bra.uni " L ";\n" L "D:\n"
__device__ __forceinline__ uint32_t t0_addr() {
  extern __shared__ __align__(1024) uint8_t smem_raw[];
  return smem_u32(smem_raw) + BAR_OFF + B_T0;
}
__device__ __forceinline__ void mbar_wait(uint32_t bar, uint32_t parity) {
  asm volatile("{\n.reg .pred p;\n.reg .u32 t0, t1;\n"
               "mbarrier.try_wait.parity.shared::cta.b64 p, [%0], %1;\n@p bra.uni WD;\n"
               WAIT_LOOP("W", "%0", "%1", "%2") "}"
               ::"r"(bar), "r"(parity), "r"(t0_addr()) : "memory");
}
__device__ __forceinline__ void mbar_wait2(uint32_t b0, uint32_t p0, uint32_t b1, uint32_t p1) {
  asm volatile("{\n.reg .pred p, q;\n.reg .u32 t0, t1;\n"
               "mbarrier.try_wait.parity.shared::cta.b64 p, [%0], %1;\nmbarrier.try_wait.parity.shared::cta.b64 q, [%2], %3;\n"
               "and.pred p, p, q;\n@p bra.uni VD;\n"
               WAIT_LOOP("W", "%0", "%1", "%4") WAIT_LOOP("V", "%2", "%3", "%4") "}"
               ::"r"(b0), "r"(p0), "r"(b1), "r"(p1), "r"(t0_addr()) : "memory");
}
__device__ __forceinline__ void tma_store_o(const CUtensorMap* m, int c2, int c3, uint32_t src) {
  asm volatile("cp.async.bulk.tensor.4d.global.shared::cta.bulk_group [%0, {%2, %2, %3, %4}], [%1];"
               ::"l"(m), "r"(src), "r"(0), "r"(c2), "r"(c3) : "memory");
}
__device__ __forceinline__ void tma_store_2d(const CUtensorMap* m, int c0, int c1, uint32_t src) {
  asm volatile("cp.async.bulk.tensor.2d.global.shared::cta.bulk_group [%0, {%2, %3}], [%1];"
               ::"l"(m), "r"(src), "r"(c0), "r"(c1) : "memory");
}
__device__ __forceinline__ void tma_add_2d(const CUtensorMap* m, int c0, int c1, uint32_t src) {
  asm volatile("cp.reduce.async.bulk.tensor.2d.global.shared::cta.add.tile.bulk_group [%0, {%2, %3}], [%1];"
               ::"l"(m), "r"(src), "r"(c0), "r"(c1) : "memory");
}
#define ELECT_BEGIN "{\n.reg .pred p;\nelect.sync _|p, 0xffffffff;\n"
__device__ __forceinline__ void e_expect(uint32_t bar, uint32_t bytes) {
  asm volatile(ELECT_BEGIN "@p mbarrier.arrive.expect_tx.shared::cta.b64 _, [%0], %1;\n}" ::"r"(bar), "r"(bytes) : "memory");
}
__device__ __forceinline__ void e_arrive2(uint32_t bar, uint32_t rbar) {
  asm volatile(ELECT_BEGIN "@p mbarrier.arrive.shared::cta.b64 _, [%0];\n@p mbarrier.arrive.shared::cluster.b64 _, [%1];\n}"
               ::"r"(bar), "r"(rbar) : "memory");
}
__device__ __forceinline__ void e_load_2d(uint32_t dst, const CUtensorMap* m, int c0, int c1, uint32_t bar) {
  asm volatile(ELECT_BEGIN "@p cp.async.bulk.tensor.2d.shared::cluster.global.mbarrier::complete_tx::bytes [%0], [%1, {%3, %4}], [%2];\n}"
               ::"r"(dst), "l"(m), "r"(bar), "r"(c0), "r"(c1) : "memory");
}
__device__ __forceinline__ void e_load_3d(uint32_t dst, const CUtensorMap* m, int c0, int c1, int c2, uint32_t bar) {
  asm volatile(ELECT_BEGIN "@p cp.async.bulk.tensor.3d.shared::cluster.global.mbarrier::complete_tx::bytes [%0], [%1, {%3, %4, %5}], [%2];\n}"
               ::"r"(dst), "l"(m), "r"(bar), "r"(c0), "r"(c1), "r"(c2) : "memory");
}
__device__ __forceinline__ void e_load_3d_hint(uint32_t dst, const CUtensorMap* m, int c0, int c1, int c2, uint32_t bar, uint64_t pol) {
  asm volatile(ELECT_BEGIN "@p cp.async.bulk.tensor.3d.shared::cluster.global.mbarrier::complete_tx::bytes.L2::cache_hint [%0], [%1, {%3, %4, %5}], [%2], %6;\n}"
               ::"r"(dst), "l"(m), "r"(bar), "r"(c0), "r"(c1), "r"(c2), "l"(pol) : "memory");
}
__device__ __forceinline__ void e_load_3d_mc(uint32_t dst, const CUtensorMap* m, int c0, int c1, int c2, uint32_t bar) {
  asm volatile(ELECT_BEGIN "@p cp.async.bulk.tensor.3d.shared::cluster.global.mbarrier::complete_tx::bytes.multicast::cluster [%0], [%1, {%3, %4, %5}], [%2], %6;\n}"
               ::"r"(dst), "l"(m), "r"(bar), "r"(c0), "r"(c1), "r"(c2), "h"((uint16_t)3) : "memory");
}
__device__ __forceinline__ void e_pf_3d(const CUtensorMap* m, int c0, int c1, int c2) {
  asm volatile(ELECT_BEGIN "@p cp.async.bulk.prefetch.tensor.3d.L2.global.tile [%0, {%1, %2, %3}];\n}" ::"l"(m), "r"(c0), "r"(c1), "r"(c2) : "memory");
}
__device__ __forceinline__ void e_load_o(uint32_t dst, const CUtensorMap* m, int c3, uint32_t bar) {
  asm volatile(ELECT_BEGIN "@p cp.async.bulk.tensor.4d.shared::cluster.global.mbarrier::complete_tx::bytes [%0], [%1, {%3, %3, %3, %4}], [%2];\n}"
               ::"r"(dst), "l"(m), "r"(bar), "r"(0), "r"(c3) : "memory");
}
__device__ __forceinline__ void e_load_o_mc(uint32_t dst, const CUtensorMap* m, int c3, uint32_t bar) {
  asm volatile(ELECT_BEGIN "@p cp.async.bulk.tensor.4d.shared::cluster.global.mbarrier::complete_tx::bytes.multicast::cluster [%0], [%1, {%3, %3, %3, %4}], [%2], %5;\n}"
               ::"r"(dst), "l"(m), "r"(bar), "r"(0), "r"(c3), "h"((uint16_t)3) : "memory");
}
__device__ __forceinline__ void st_async(uint32_t a, int v, uint32_t bar) {
  asm volatile("st.async.shared::cluster.mbarrier::complete_tx::bytes.s32 [%0], %1, [%2];" ::"r"(a), "r"(v), "r"(bar) : "memory");
}
__device__ __forceinline__ uint32_t mapa(uint32_t a, uint32_t rank) {
  uint32_t r; asm volatile("mapa.shared::cluster.u32 %0, %1, %2;" : "=r"(r) : "r"(a), "r"(rank)); return r;
}
__device__ __forceinline__ void cluster_sync() {
  asm volatile("barrier.cluster.arrive.relaxed.aligned;\nbarrier.cluster.wait.aligned;" ::: "memory");
}
__device__ __forceinline__ unsigned int ld_rlx(const unsigned int* p) {
  unsigned int v;
  asm volatile("ld.relaxed.gpu.global.u32 %0, [%1];" : "=r"(v) : "l"(p) : "memory");
  return v;
}
__device__ __forceinline__ unsigned int ld_flag(const unsigned int* fp) {
  unsigned int v;
  asm volatile("ld.acquire.gpu.global.u32 %0, [%1];" : "=r"(v) : "l"(fp) : "memory");
  return v;
}
__device__ __forceinline__ int wait_flag(const unsigned int* fp, unsigned int v, const unsigned int target) {
  while (__any_sync(0xffffffffu, (v >> 11) != target)) {
    if (__any_sync(0xffffffffu, deadline_passed())) break;
    __nanosleep(40);
    v = ld_flag(fp);
  }
  asm volatile("fence.proxy.async.global;" ::: "memory");
  return (int)(v & 0x7ffu);
}
__device__ __forceinline__ void release_slot(const int s) {
  if (s < NITEMS && atomicInc(&g_cons[s], 2u) == 2u) atomicAnd(&g_busy[s >> 5], ~(1u << (s & 31)));
}
__device__ __forceinline__ void publish(const int item, const int slot, const unsigned int old) {
  const unsigned int d = (2u << 11) + (unsigned int)slot - (old & 0x7ffu);
  asm volatile("red.release.gpu.global.add.u32 [%0], %1;" ::"l"(&g_flags[item]), "r"(d) : "memory");
}
__device__ __forceinline__ void wg_fence() { asm volatile("wgmma.fence.sync.aligned;" ::: "memory"); }
__device__ __forceinline__ void wg_commit() { asm volatile("wgmma.commit_group.sync.aligned;" ::: "memory"); }
template <int N> __device__ __forceinline__ void wg_wait() { asm volatile("wgmma.wait_group.sync.aligned %0;" ::"n"(N) : "memory"); }
__device__ __forceinline__ void fence_async_smem() { asm volatile("fence.proxy.async.shared::cta;" ::: "memory"); }
__device__ __forceinline__ void named_bar(int id, int n) { asm volatile("bar.sync %0, %1;" ::"r"(id), "r"(n) : "memory"); }
__device__ __forceinline__ uint32_t tid_now() { uint32_t t; asm volatile("mov.u32 %0, %tid.x;" : "=r"(t)); return t; }
__device__ __forceinline__ void arrive_lane0(uint32_t bar) {
  asm volatile("{\n.reg .pred p;\nelect.sync _|p, 0xffffffff;\n@p mbarrier.arrive.shared::cta.b64 _, [%0];\n}" ::"r"(bar) : "memory");
}
__device__ __forceinline__ float rcp(float x) { float y; asm("rcp.approx.ftz.f32 %0, %1;" : "=f"(y) : "f"(x)); return y; }
__device__ __forceinline__ float ex2(float x) { float y; asm("ex2.approx.ftz.f32 %0, %1;" : "=f"(y) : "f"(x)); return y; }
__device__ __forceinline__ uint32_t pack_bf16(float lo, float hi) {
  uint32_t r; asm("cvt.rn.bf16x2.f32 %0, %1, %2;" : "=r"(r) : "f"(hi), "f"(lo)); return r;
}
__device__ __forceinline__ void stsm_x4_t(uint32_t addr, uint32_t r0, uint32_t r1, uint32_t r2, uint32_t r3) {
  asm volatile("stmatrix.sync.aligned.m8n8.x4.trans.shared.b16 [%0], {%1, %2, %3, %4};" ::"r"(addr), "r"(r0), "r"(r1), "r"(r2), "r"(r3) : "memory");
}
__device__ __forceinline__ int lds_s32(uint32_t a) { int v; asm volatile("ld.shared.s32 %0, [%1];" : "=r"(v) : "r"(a) : "memory"); return v; }
__device__ __forceinline__ void sts_s32(uint32_t a, int v) { asm volatile("st.shared.s32 [%0], %1;" ::"r"(a), "r"(v) : "memory"); }
__device__ __forceinline__ void sts_f32(uint32_t a, float v) { asm volatile("st.shared.f32 [%0], %1;" ::"r"(a), "f"(v) : "memory"); }

#define ACC_STR                                                                        \
  "{%0, %1, %2, %3, %4, %5, %6, %7, %8, %9, %10, %11, %12, %13, %14, %15, "            \
  "%16, %17, %18, %19, %20, %21, %22, %23, %24, %25, %26, %27, %28, %29, %30, %31, "   \
  "%32, %33, %34, %35, %36, %37, %38, %39, %40, %41, %42, %43, %44, %45, %46, %47, "   \
  "%48, %49, %50, %51, %52, %53, %54, %55, %56, %57, %58, %59, %60, %61, %62, %63, "   \
  "%64, %65, %66, %67, %68, %69, %70, %71, %72, %73, %74, %75, %76, %77, %78, %79}, "
#define ACC8(C, d, o) C(d[o]), C(d[o + 1]), C(d[o + 2]), C(d[o + 3]), C(d[o + 4]), C(d[o + 5]), C(d[o + 6]), C(d[o + 7])
#define ACC_OPS(C, d) ACC8(C, d, 0), ACC8(C, d, 8), ACC8(C, d, 16), ACC8(C, d, 24), ACC8(C, d, 32), ACC8(C, d, 40), ACC8(C, d, 48), \
                      ACC8(C, d, 56), ACC8(C, d, 64), ACC8(C, d, 72)

#define DESC_STR "{\n.reg .b32 x, y, h;\n.reg .b64 a, b;\n.reg .pred p;\nadd.u32 x, %80, %81;\nadd.u32 y, %82, %83;\nmov.b32 h, 0x40000040;\n" \
                 "mov.b64 a, {x, h};\nmov.b64 b, {y, h};\n"
template <int TA, bool INIT, int IA, int IB>
__device__ __forceinline__ void wgmma(float (&d)[80], uint32_t a, uint32_t b) {
  if constexpr (INIT) {
    asm volatile(DESC_STR "wgmma.mma_async.sync.aligned.m64n160k16.f32.bf16.bf16 " ACC_STR "a, b, 0, 1, 1, %84, 0;\n}"
                 : ACC_OPS("=f", d) : "r"(a), "n"(IA), "r"(b), "n"(IB), "n"(TA));
  } else {
    asm volatile(DESC_STR "wgmma.mma_async.sync.aligned.m64n160k16.f32.bf16.bf16 " ACC_STR "a, b, 1, 1, 1, %84, 0;\n}"
                 : ACC_OPS("+f", d) : "r"(a), "n"(IA), "r"(b), "n"(IB), "n"(TA));
  }
}
template <int IA = 0, int IB = 0>
__device__ __forceinline__ void wgmma_t_p(float (&d)[80], uint32_t a, uint32_t b, uint32_t acc) {
  asm volatile(DESC_STR "setp.ne.u32 p, %84, 0;\n"
               "wgmma.mma_async.sync.aligned.m64n160k16.f32.bf16.bf16 " ACC_STR "a, b, p, 1, 1, 1, 0;\n}"
               : ACC_OPS("+f", d) : "r"(a), "n"(IA), "r"(b), "n"(IB), "r"(acc));
}
template <bool INIT, int IA, int IB, int N>
__device__ __forceinline__ void mma_t4(float (&d)[N], uint32_t a, uint32_t b) {
  wgmma<1, INIT, IA, IB>(d, a, b);
  wgmma<1, false, IA + 128, IB + 2>(d, a, b);
  wgmma<1, false, IA + 256, IB + 4>(d, a, b);
  wgmma<1, false, IA + 384, IB + 6>(d, a, b);
}
template <bool INIT, int IA, int IB, int N>
__device__ __forceinline__ void mma_n4(float (&d)[N], uint32_t a, uint32_t b) {
  wgmma<0, INIT, IA, IB>(d, a, b);
  wgmma<0, false, IA + 2, IB + 2>(d, a, b);
  wgmma<0, false, IA + 4, IB + 4>(d, a, b);
  wgmma<0, false, IA + 6, IB + 6>(d, a, b);
}
template <int V> struct IntC { static constexpr int value = V; };
__device__ __forceinline__ bool wg_any(int id, bool v) {
  uint32_t r;
  asm volatile("{\n.reg .pred p, q;\nsetp.ne.u32 q, %2, 0;\nbarrier.cta.red.or.pred p, %1, 128, q;\nselp.u32 %0, 1, 0, p;\n}"
               : "=r"(r) : "r"(id), "r"((uint32_t)v) : "memory");
  return __shfl_sync(0xffffffffu, r, 0) != 0;
}
__device__ __forceinline__ void job_bh(int j, int& b, int& h) {
  b = ((j >> 5) & 15) * 2 + (int)(blockIdx.x & 1);
  h = j & 31;
}
constexpr uint32_t PAIR_SIDE = 0xcb2cu;
constexpr int QLEN = NJOBS / 2 + 8;
struct Sched {
  int kl;
  int zero;
  int stag, stag0;
  int pfn1, pft;
  int hja, hjb, hjr, hk, hth, htp, hmax;
  int aff, dbal, np, rf, pwo, pw, rs;
  const __nv_bfloat16* kp;
  const __nv_bfloat16* vp;
  const __nv_bfloat16* xp;
  const __nv_bfloat16* wp;
  uint4* out;
  uint8_t* o;
  short order[2][QLEN];
};
template <int N> __device__ __forceinline__ void fence_regs(float (&d)[N]) {
#pragma unroll
  for (int i = 0; i < N; i++) asm volatile("" : "+f"(d[i])::"memory");
}
template <bool V> struct BoolC { static constexpr bool value = V; };
constexpr float SM_SCALE = 0.08838834764831845f * 1.4426950408889634f;
__device__ __forceinline__ uint32_t tab(uint64_t t, int i) { return ((uint32_t)(t >> (8 * i)) & 0xffu) << 12; }

__device__ __forceinline__ uint32_t stsm_lane_off() {
  const uint32_t t = tid_now();
  const uint32_t i = t & 7, m = (t >> 3) & 3, w = (t >> 5) & 3;
  return ((m >> 1) * 8 + i) * 128 + (((2 * w + (m & 1)) ^ i) << 4);
}

__device__ __forceinline__ uint32_t lane_off_tid(uint32_t o) {
  asm volatile("" : "+r"(o));
  const uint32_t i = (o >> 7) & 7, x = ((o >> 4) & 7) ^ i;
  return i | ((x & 1) << 3) | ((o >> 6) & 16) | ((x >> 1) << 5);
}

__device__ __forceinline__ void slow_item(uint8_t* o0, const int dh, const __nv_bfloat16* __restrict__ kp, const __nv_bfloat16* __restrict__ vp,
                                          const __nv_bfloat16* __restrict__ xp, const __nv_bfloat16* __restrict__ wp, const int nq) {
  const int lane = threadIdx.x & 31, warp = __shfl_sync(0xffffffffu, threadIdx.x >> 5, 0);
  for (int q = warp * nq; q < warp * nq + nq; q++) {
    uint8_t* qo = o0 + (q / 40) * 16384 + (q % 40) * 128;
    uint2* qw = reinterpret_cast<uint2*>(qo + (lane >> 4) * dh + (lane & 15) * 8);
    {
      float q0 = 0.f, q1 = 0.f, q2 = 0.f, q3 = 0.f;
#pragma unroll 4
      for (int k = 0; k < DM; k++) {
        const float xv = __bfloat162float(xp[q * DM + k]);
        const uint2 w = *reinterpret_cast<const uint2*>(wp + (size_t)k * (NH * DH) + lane * 4);
        q0 = fmaf(xv, __uint_as_float(w.x << 16), q0); q1 = fmaf(xv, __uint_as_float(w.x & 0xffff0000u), q1);
        q2 = fmaf(xv, __uint_as_float(w.y << 16), q2); q3 = fmaf(xv, __uint_as_float(w.y & 0xffff0000u), q3);
      }
      __stcg(qw, make_uint2(pack_bf16(q0 * SM_SCALE, q1 * SM_SCALE), pack_bf16(q2 * SM_SCALE, q3 * SM_SCALE)));
      __threadfence_block();
      __syncwarp();
    }
    float s[16];
#pragma unroll
    for (int j = 0; j < 16; j++) s[j] = 0.f;
    for (int d = 0; d < 16; d++) {
      const uint4 qq = __ldcg(reinterpret_cast<const uint4*>(qo + (d >> 3) * dh + (d & 7) * 16));
      const uint32_t qv[4] = {qq.x, qq.y, qq.z, qq.w};
#pragma unroll
      for (int j = 0; j < 16; j++) {
        const uint4 kv = *reinterpret_cast<const uint4*>(kp + (size_t)(lane + 32 * j) * DH + d * 8);
        const uint32_t kk[4] = {kv.x, kv.y, kv.z, kv.w};
#pragma unroll
        for (int e = 0; e < 4; e++) {
          s[j] = fmaf(__uint_as_float(qv[e] << 16), __uint_as_float(kk[e] << 16), s[j]);
          s[j] = fmaf(__uint_as_float(qv[e] & 0xffff0000u), __uint_as_float(kk[e] & 0xffff0000u), s[j]);
        }
      }
    }
    float m = s[0];
#pragma unroll
    for (int j = 1; j < 16; j++) m = fmaxf(m, s[j]);
    for (int o = 16; o > 0; o >>= 1) m = fmaxf(m, __shfl_xor_sync(0xffffffffu, m, o));
    float l = 0.f;
#pragma unroll
    for (int j = 0; j < 16; j++) {
      s[j] = ex2(s[j] - m);
      l += s[j];
    }
    for (int o = 16; o > 0; o >>= 1) l += __shfl_xor_sync(0xffffffffu, l, o);
    float o0 = 0.f, o1 = 0.f, o2 = 0.f, o3 = 0.f;
#pragma unroll
    for (int j = 0; j < 16; j++) {
#pragma unroll 4
      for (int src = 0; src < 32; src++) {
        const float p = __shfl_sync(0xffffffffu, s[j], src);
        const uint2 vv = *reinterpret_cast<const uint2*>(vp + (size_t)(src + 32 * j) * DH + lane * 4);
        o0 = fmaf(p, __uint_as_float(vv.x << 16), o0); o1 = fmaf(p, __uint_as_float(vv.x & 0xffff0000u), o1);
        o2 = fmaf(p, __uint_as_float(vv.y << 16), o2); o3 = fmaf(p, __uint_as_float(vv.y & 0xffff0000u), o3);
      }
    }
    const float il = 1.f / l;
    __syncwarp();
    *qw = make_uint2(pack_bf16(o0 * il, o1 * il), pack_bf16(o2 * il, o3 * il));
  }
}

#define EA 2
#define EB 5
#define EC 8
#define ECE 3
#define OPEND 1
#define EC0 3
#define SPLIT0 2
#define SPLIT1 8
#define TIDX lane_off_tid(lane_off)
#define SPLIT2 14
__device__ __forceinline__ void sched_boundary(const int zero) {
  for (int i = zero; i > 0; i--) asm volatile("nanosleep.u32 0;");
}
__device__ __forceinline__ unsigned int lat(uint8_t* p) {
  unsigned int t0, t1, v;
  asm volatile("mov.u32 %0, %clock;" : "=r"(t0)::"memory");
  asm volatile("atom.global.add.u32 %0, [%1], 0;" : "=r"(v) : "l"(p) : "memory");
  if (v == 0x12345u) t0 = 0;
  asm volatile("mov.u32 %0, %clock;" : "=r"(t1)::"memory");
  return t1 - t0;
}
__device__ __forceinline__ bool far_line(uint8_t* p, const int n) {
  unsigned int l0 = ~0u, l1 = ~0u;
  for (int i = 0; i < n; i++) { l0 = min(l0, lat(p)); l1 = min(l1, lat(p + 8192)); }
  return l0 > l1;
}
__device__ __forceinline__ uint32_t tab8(uint64_t t, int i) { return ((uint32_t)(t >> (8 * i)) & 0xffu) << 8; }
__device__ __forceinline__ int a_role(const uint32_t base, const int wg, const Sched& sc, float (&accS)[80], float (&accO)[80]) {
  const uint32_t bar = base + BAR_OFF;
  const uint32_t dbase = (base >> 4) | 0x10000u;
  const uint32_t dbw = dbase + wg * 512;
  const float cs = SM_SCALE;
  uint32_t tph = 0;
  auto qstep = [&](auto cc, const uint32_t ph) __attribute__((always_inline)) {
    constexpr int c = decltype(cc)::value, so = q_reg(c) * (Q_STAGE >> 4);
    mbar_wait(bar + B_QF + 8 * c, ph);
    wg_fence();
    mma_t4<c == 0, so + 1280, so>(accS, dbw, dbase);
    wg_commit();
  };
  auto p_done = [&](const int t) {
    fence_async_smem();
    __syncwarp();
    arrive_lane0(bar + B_PF + 8 * t);
  };
  float l[40];
  if (wg == 1) arrive_lane0(bar + B_TOK);
  auto prologue = [&](auto& S, const uint32_t dx) __attribute__((always_inline)) {
    mbar_wait(bar + B_QF, 0);
    if (threadIdx.x == 64) PROF_X(2, 8);
    wg_fence();
    mma_t4<true, 1280, 0>(S, dbw, dx);
    wg_commit();
#pragma unroll 1
    for (int c = 1; c < 10; c++) {
      const uint32_t so = q_reg(c) * (Q_STAGE >> 4);
      mbar_wait(bar + B_QF + 8 * c, 0);
      wg_fence();
      mma_t4<false, 1280, 0>(S, dbw + so, dx + so);
      wg_commit();
      wg_wait<1>();
      arrive_lane0(bar + B_QE + 8 * (c - 1));
    }
  };
  int r = 0;
  prologue(accS, dbase);
#pragma unroll
  for (int j = 0; j < 80; j++) accO[j] = 0.f;
  float (&S)[80] = accS, (&O)[80] = accO;
#pragma unroll 1
  for (;; r++) {
    constexpr int NJ = 20, NS = 10, SP0 = SPLIT0, SP1 = SPLIT1, SP2 = SPLIT2;
    auto pv = [&](const int t) {
      const uint32_t da = dbw + tab8(TAB_V, t), db = dbase + tab8(TAB_P, t);
      wg_fence();
      wgmma_t_p(O, da, db, t);
      wgmma<1, false, 128, 2>(O, da, db);
      wgmma<1, false, 256, 4>(O, da, db);
      wgmma<1, false, 384, 6>(O, da, db);
      wg_commit();
    };
    const uint32_t ph = r & 1;
    const bool last = wg_any(1 + wg, lds_s32(bar + B_ITEMQ + ((r + 1) & 3) * 4) < 0 || r >= 64);
    if (r > 0) mbar_wait(bar + B_OE + wg * D_OE, ph ^ 1);
    const uint32_t lane_off = stsm_lane_off();
    wg_wait<0>();
    fence_regs(S);
    arrive_lane0(bar + B_QE + 72);
    PROF_T(r * 3 + 1); PROF_G((r * 3 >= 33 ? 33 : r * 3) + 16); PROF_D(40); PROF_D(41);
    {
      const uint32_t a = base + QO_OFF + wg * 20480 + lane_off;
      const float qs = cs;
#pragma unroll
      for (int j = 0; j < NJ; j += 2)
        stsm_x4_t(a + j * 1024, pack_bf16(S[4 * j] * qs, S[4 * j + 1] * qs), pack_bf16(S[4 * j + 2] * qs, S[4 * j + 3] * qs),
                  pack_bf16(S[4 * j + 4] * qs, S[4 * j + 5] * qs), pack_bf16(S[4 * j + 6] * qs, S[4 * j + 7] * qs));
    }
    fence_async_smem();
    __syncwarp();
    arrive_lane0(bar + B_QRDY + 8 * wg);
    mbar_wait(bar + B_QRDY, ph);
    auto tile = [&](const int T, auto firstc) {
      constexpr bool FIRST = decltype(firstc)::value;
      const uint32_t dk = dbase + tab8(TAB_K, T);
      PROF_D(T * 4);
      mbar_wait2(bar + B_KF + 8 * T, ph, bar + B_TOK + 8 * wg, tph); tph ^= 1;
      PROF_D(T * 4 + 1);
      wg_fence();
      mma_n4<true, 0, (QO_OFF >> 4)>(S, dk, dbase);
      if constexpr (FIRST) {
        wg_commit();
        mbar_wait(bar + B_QRDY + 8, ph);
        wg_fence();
      }
      mma_n4<false, 512, (QO_OFF >> 4) + 1280>(S, dk, dbase);
      wg_commit();
      const uint32_t a = base + (tab8(TAB_P, T) << 4) + lane_off;
      if constexpr (FIRST) {
        arrive_lane0(bar + B_TOK + 8 * (wg ^ 1));
        wg_wait<0>();
        fence_regs(S);
      } else {
        p_done(T - 2);
        if (T >= 3) pv(T - 3); else { wg_fence(); wg_commit(); }
        mbar_wait2(bar + B_VF + 8 * (T - 2), ph, bar + B_PF + 8 * (T - 2), ph);
        wg_wait<1>();
        fence_regs(S);
        pv(T - 2);
        arrive_lane0(bar + B_TOK + 8 * (wg ^ 1));
      }
      PROF_D(T * 4 + 2);
      arrive_lane0(bar + B_KE + 8 * T);
      uint32_t p[2 * NJ];
      auto sm = [&](const int j) {
        const float e0 = ex2(S[4 * j]), e1 = ex2(S[4 * j + 1]), e2 = ex2(S[4 * j + 2]), e3 = ex2(S[4 * j + 3]);
        p[2 * j] = pack_bf16(e0, e1); p[2 * j + 1] = pack_bf16(e2, e3);
        if constexpr (FIRST) { l[2 * j] = e0 + e2; l[2 * j + 1] = e1 + e3; }
        else { l[2 * j] += e0; l[2 * j + 1] += e1; l[2 * j] += e2; l[2 * j + 1] += e3; }
      };
      if constexpr (FIRST) {
#pragma unroll
        for (int j = 0; j < NJ; j++) {
          sm(j);
          if (j == 1 && wg == 1) mbar_wait(bar + B_KE, ph);
          if (j & 1) stsm_x4_t(a + (j - 1) * 1024, p[2 * j - 2], p[2 * j - 1], p[2 * j], p[2 * j + 1]);
        }
      } else {
#pragma unroll
        for (int j = 0; j < SP0; j++) sm(j);
        sched_boundary(sc.zero);
#pragma unroll
        for (int j = SP0; j < SP1; j++) sm(j);
        sched_boundary(sc.zero);
        wg_wait<1>();
        arrive_lane0(bar + B_PVD + 8 * (T - 3));
#pragma unroll
        for (int j = SP1; j < SP2; j++) sm(j);
        mbar_wait(bar + B_PVD + 8 * (T - 3), ph);
        wg_wait<0>();
        arrive_lane0(bar + B_PVD + 8 * (T - 2));
#pragma unroll
        for (int j = SP2; j < NJ; j++) {
          sm(j);
          constexpr int per = (NS + (NJ - SP2) - 1) / (NJ - SP2);
#pragma unroll
          for (int e = 0; e < per; e++) {
            const int q = (j - SP2) * per + e;
            if (q < NS && 2 * q + 1 <= j && j < NJ - 1) stsm_x4_t(a + q * 2048, p[4 * q], p[4 * q + 1], p[4 * q + 2], p[4 * q + 3]);
          }
        }
#pragma unroll
        for (int q = 0; q < NS; q++) {
          constexpr int per = (NS + (NJ - SP2) - 1) / (NJ - SP2);
          const int j = SP2 + q / per;
          if (!(2 * q + 1 <= j && j < NJ - 1)) stsm_x4_t(a + q * 2048, p[4 * q], p[4 * q + 1], p[4 * q + 2], p[4 * q + 3]);
        }
      }
      PROF_D(T * 4 + 3);
    };
    tile(wg, BoolC<true>{});
#pragma unroll 1
    for (int T = wg + 2; T < 8; T += 2) tile(T, BoolC<false>{});
    mbar_wait(bar + B_TOK + 8 * wg, tph); tph ^= 1;
    pv(5 + wg);
    p_done(6 + wg);
    mbar_wait2(bar + B_VF + 8 * (6 + wg), ph, bar + B_PF + 8 * (6 + wg), ph);
    pv(6 + wg);
    arrive_lane0(bar + B_TOK + 8 * (wg ^ 1));
    PROF_D(32);
    auto bf1 = [&]() {
      sched_boundary(sc.zero);
      const bool b4 = TIDX & 16;
#pragma unroll
      for (int j = 0; j < 20; j++) {
        const float snd = b4 ? l[j] : l[j + 20], kp = b4 ? l[j + 20] : l[j];
        l[j] = kp + __shfl_xor_sync(0xffffffffu, snd, 16);
      }
      sched_boundary(sc.zero);
      PROF_D(37);
    };
    auto bf2 = [&]() {
      const uint32_t t = TIDX;
      const bool b4 = t & 16, b3 = t & 8, b2 = t & 4;
#pragma unroll
      for (int j = 0; j < 10; j++) {
        const float snd = b3 ? l[j] : l[j + 10], kp = b3 ? l[j + 10] : l[j];
        l[j] = kp + __shfl_xor_sync(0xffffffffu, snd, 8);
      }
#pragma unroll
      for (int j = 0; j < 5; j++) {
        const float snd = b2 ? l[j] : l[j + 5], kp = b2 ? l[j + 5] : l[j];
        l[j] = kp + __shfl_xor_sync(0xffffffffu, snd, 4);
      }
      const uint32_t i0 = (b4 ? 20 : 0) + (b3 ? 10 : 0) + (b2 ? 5 : 0);
      const uint32_t a = base + LP_OFF + wg * 2560 + ((t >> 5) & 3) * 640 + i0 * 16 + (t & 3) * 4;
#pragma unroll
      for (int j = 0; j < 5; j++) sts_f32(a + j * 16, l[j]);
      __syncwarp();
      arrive_lane0(bar + B_LP);
      PROF_D(33);
    };
    auto pv7 = [&]() {
      if (wg == 0) {
        mbar_wait2(bar + B_VF + 56, ph, bar + B_PF + 56, ph);
        pv(7);
      }
    };
    auto epi_begin = [&](const bool more) -> bool {
      if (more) mbar_wait2(bar + B_LI, ph, bar + B_QE + 8, ph ^ 1);
      else mbar_wait(bar + B_LI, ph);
      const bool bad = lds_s32(bar + B_BAD) & 1;
      const uint32_t li = base + LI_OFF + (TIDX & 3) * 160;
#pragma unroll
      for (int j = 0; j < NS; j++)
        asm volatile("ld.shared.v4.f32 {%0, %1, %2, %3}, [%4];" : "=f"(l[4 * j]), "=f"(l[4 * j + 1]), "=f"(l[4 * j + 2]), "=f"(l[4 * j + 3])
                     : "r"(li + j * 16) : "memory");
      return bad;
    };
    auto epi = [&](const int q0, const int q1) {
      const uint32_t a = base + QO_OFF + wg * 20480 + lane_off;
#pragma unroll
      for (int j = 2 * q0; j < (2 * q1 < NJ ? 2 * q1 : NJ); j += 2) {
        const float i0 = l[2 * j], i1 = l[2 * j + 1], i2 = l[2 * j + 2], i3 = l[2 * j + 3];
        stsm_x4_t(a + j * 1024, pack_bf16(O[4 * j] * i0, O[4 * j + 1] * i1), pack_bf16(O[4 * j + 2] * i0, O[4 * j + 3] * i1),
                  pack_bf16(O[4 * j + 4] * i2, O[4 * j + 5] * i3), pack_bf16(O[4 * j + 6] * i2, O[4 * j + 7] * i3));
      }
    };
    auto epi_end = [&]() {
      fence_async_smem();
      __syncwarp();
      arrive_lane0(bar + B_OF + wg * D_OF);
      PROF_T(r * 3 + 2); PROF_G(62); PROF_T(63); PROF_D(42);
    };
    if (last) {
      bf1();
      bf2();
      pv7();
      wg_wait<0>();
      fence_regs(O);
      arrive_lane0(bar + B_AD);
      if (!epi_begin(false)) epi(0, 10);
      epi_end();
      break;
    }
    qstep(IntC<0>{}, ph ^ 1);
    PROF_D(39);
    wg_wait<2>();
    arrive_lane0(bar + B_PVD + 8 * (5 + wg));
    PROF_D(38);
    bf1();
    wg_wait<1>();
    arrive_lane0(bar + B_PVD + 8 * (6 + wg));
    qstep(IntC<1>{}, ph ^ 1);
    sched_boundary(sc.zero);
    bf2();
    pv7();
    PROF_D(34);
    qstep(IntC<2>{}, ph ^ 1);
    PROF_D(35);
    wg_wait<1>();
    fence_regs(O);
    if (wg == 0) arrive_lane0(bar + B_PVD + 56);
    arrive_lane0(bar + B_QE);
    arrive_lane0(bar + B_QE + 8);
    PROF_D(36);
    bool bad = false;
    auto step = [&](auto cc) {
      constexpr int c = decltype(cc)::value;
      qstep(cc, ph ^ 1);
      PROF_D((wg ^ 1) * 4 + ((c - 3) >> 2) * 8 + ((c - 3) & 3));
      wg_wait<1>();
      arrive_lane0(bar + B_QE + 8 * (c - 1));
      if (c == EC0) bad = epi_begin(true);
      if (c == EC0 && !bad) epi(0, EA);
      if (c == EC0 + 1 && !bad) epi(EA, EB);
      if (c == EC0 + 2 && !bad) epi(EB, EC);
      if (c == EC0 + 3 && !bad) epi(EC, 10);
      if (c == EC0 + ECE) epi_end();
    };
    step(IntC<3>{}); step(IntC<4>{}); step(IntC<5>{}); step(IntC<6>{}); step(IntC<7>{}); step(IntC<8>{}); step(IntC<9>{});
  }
  return r + 1;
}

__device__ __forceinline__ bool p_unit(const int q, int& pg, int& pj) {
  const int g = (q * 205) >> 10, pk = q - 5 * g, rank = blockIdx.x & 1;
  pg = g * 2 + (pk == 4 ? rank : (pk >> 1));
  pj = pk == 4 ? 4 : (pk & 1) * 2 + rank;
  return pk == 4;
}
__device__ __forceinline__ void p_role(const uint32_t base, const int wg, uint32_t ph, float (&accS)[80], float (&accO)[80]) {
  const uint32_t bar = base + BAR_OFF, p_full = bar + B_PFULL, p_empty = bar + B_PEMPTY;
  uint32_t st = 0, prev = bar + B_NOP;
#pragma unroll
  for (int j = 0; j < 80; j++) accS[j] = accO[j] = 0.f;
  mbar_wait(bar + B_HB, 0);
  const uint32_t k0 = __shfl_sync(0xffffffffu, lds_s32(bar + B_DEC), 0) & 6;
  int code = __shfl_sync(0xffffffffu, lds_s32(bar + B_HQ + (k0 & 3) * 4), 0), nxt = lds_s32(bar + B_HQ + (k0 & 3) * 4 + 4);
  ph ^= (k0 >> 1) & 1;
  PROF_G(54);
#pragma unroll 1
  for (uint32_t k = k0 + 2; code >= 0 && k < 202; k++) {
    mbar_wait(p_full + 8 * st, ph);
    const uint32_t s = base + st * P_STAGE;
    const uint32_t db = (s >> 4) | 0x10000u, da = db + wg * 512;
    code = __shfl_sync(0xffffffffu, nxt, 0);
    if (code < C_OUT) {
      wg_fence();
      mma_t4<false, 2560, 0>(accS, da, db);
      mma_t4<false, 2560, 1280>(accO, da, db);
      wg_commit();
      wg_wait<1>();
      arrive_lane0(prev);
      mbar_wait(p_full + 8 * st + 8, ph);
      wg_fence();
      mma_t4<false, 2560 + (P_STAGE >> 4), (P_STAGE >> 4)>(accS, da, db);
      mma_t4<false, 2560 + (P_STAGE >> 4), 1280 + (P_STAGE >> 4)>(accO, da, db);
      wg_commit();
      wg_wait<1>();
      arrive_lane0(p_empty + 8 * st);
      prev = p_empty + 8 * st + 8;
    } else {
      nxt = __shfl_sync(0xffffffffu, lds_s32(bar + B_HQ + (k & 3) * 4), 0);
      const bool fin = nxt < 0;
      wg_fence();
      mma_t4<false, 2560, 0>(accS, da, db);
      wg_commit();
      wg_wait<1>();
      arrive_lane0(prev);
      if (!fin) {
        wg_fence();
        mma_t4<false, 2560, 1280>(accO, da, db);
        wg_commit();
      }
      prev = bar + B_NOP;
      mbar_wait(p_full + 8 * st + 8, ph);
      wg_fence();
      mma_t4<false, 2560 + (P_STAGE >> 4), (P_STAGE >> 4)>(accS, da, db);
      wg_commit();
      const uint32_t pe = p_empty + 8 * st, so = fin ? 0 : P_STAGE >> 4;
      wg_wait<1>();
      arrive_lane0(fin ? prev : pe);
      wg_fence();
      mma_t4<false, 2560, 1280>(accO, da + so, db + so);
      wg_commit();
      ph ^= st >> 1;
      st ^= 2;
      k++;
      const uint32_t a = base + (st + wg) * P_STAGE + stsm_lane_off();
      mbar_wait2(p_full + 8 * st, ph, p_full + 8 * (st + wg), ph);
      mbar_wait(bar + B_FIN, 0);
      sts_s32(bar + B_STG + 4 * wg, code | ((st + wg) << 16) | (nxt & 0x80000000));
      wg_wait<1>();
      fence_regs(accS);
      PROF_T(nxt >= 0 ? 50 : 52);
      auto stage = [&](float (&d)[80], const uint32_t x, const uint32_t sig) {
#pragma unroll
        for (int j = 0; j < 20; j += 2)
          stsm_x4_t(x + j * 1024, pack_bf16(d[4 * j], d[4 * j + 1]), pack_bf16(d[4 * j + 2], d[4 * j + 3]),
                    pack_bf16(d[4 * j + 4], d[4 * j + 5]), pack_bf16(d[4 * j + 6], d[4 * j + 7]));
        fence_async_smem();
        __syncwarp();
        arrive_lane0(sig);
      };
      stage(accS, a, bar + B_QRDY + 8 * wg);
      if (fin) {
        wg_fence();
        mma_t4<false, 2560 + (P_STAGE >> 4), 1280 + (P_STAGE >> 4)>(accO, da, db);
        wg_commit();
      }
#pragma unroll
      for (int j = 0; j < 80; j++) accS[j] = 0.f;
      wg_wait<0>();
      fence_regs(accO);
      arrive_lane0(pe + 8);
      stage(accO, a + 20480, bar + B_OF + wg * D_OF);
#pragma unroll
      for (int j = 0; j < 80; j++) accO[j] = 0.f;
      PROF_T(nxt >= 0 ? 51 : 53); PROF_G(62); PROF_T(63);
      code = nxt;
    }
    nxt = lds_s32(bar + B_HQ + (k & 3) * 4);
    st ^= 2;
    if (st == 0) ph ^= 1;
  }
  wg_wait<0>();
}
__device__ __forceinline__ void p_store(const uint32_t base, uint32_t ph, const CUtensorMap* tm_out) {
  const uint32_t bar = base + BAR_OFF;
  for (int e = 0; e < 64; e++) {
    int c;
    for (int i = 0; i < 4; i++) {
      const int w = i & 1, hf = i >> 1;
      mbar_wait(bar + (hf ? B_OF + w * D_OF : B_QRDY + 8 * w), ph);
      c = lds_s32(bar + B_STG + 4 * w);
      int pg, pj; p_unit(c & 63, pg, pj);
      const uint32_t stg = base + ((c >> 16) & 3) * P_STAGE + hf * 20480;
      asm volatile("fence.proxy.async.global;" ::: "memory");
      if (c & C_RED) tma_add_2d(tm_out, pj * 128 + w * 64, pg * 320 + hf * 160, stg);
      else tma_store_2d(tm_out, pj * 128 + w * 64, pg * 320 + hf * 160, stg);
      asm volatile("cp.async.bulk.commit_group;" ::: "memory");
    }
    if (c < 0) break;
    ph ^= 1;
    const uint32_t pe = bar + B_PEMPTY + 8 * ((c >> 16) & 2);
    asm volatile("cp.async.bulk.wait_group.read 1;" ::: "memory");
    asm volatile("mbarrier.arrive.shared::cta.b64 _, [%0], 8;" ::"r"(pe) : "memory");
    asm volatile("cp.async.bulk.wait_group.read 0;" ::: "memory");
    asm volatile("mbarrier.arrive.shared::cta.b64 _, [%0], 8;" ::"r"(pe + 8) : "memory");
  }
  asm volatile("cp.async.bulk.wait_group 0;" ::: "memory");
}

__global__ void __cluster_dims__(2, 1, 1) __launch_bounds__(384, 1)
fused_kernel(const __grid_constant__ CUtensorMap tm_x, const __grid_constant__ CUtensorMap tm_wq,
             const __grid_constant__ CUtensorMap tm_k, const __grid_constant__ CUtensorMap tm_v,
             const __grid_constant__ CUtensorMap tm_o, const __grid_constant__ CUtensorMap tm_wo,
             const __grid_constant__ CUtensorMap tm_out, const __grid_constant__ CUtensorMap tm_os, const __grid_constant__ Sched sc) {
  extern __shared__ __align__(1024) uint8_t smem_raw[];
  const uint32_t base = smem_u32(smem_raw);
  const uint32_t bar = base + BAR_OFF;
  const int tid = threadIdx.x, lane = tid & 31;
  const int warp = __shfl_sync(0xffffffffu, tid >> 5, 0), wg = warp >> 2;
  const int cl = blockIdx.x >> 1, rank = blockIdx.x & 1, ncl = gridDim.x >> 1;

  const bool late = cl >= ncl - 10;
  const int q_own = 40 - ncl + cl;
  const int j3 = ((cl >> 1) * 43) >> 7, i3 = (cl >> 1) - 3 * j3;
  const int job0 = (i3 == 2 ? 4 + (cl & 1) : (cl & 1) * 2 + i3) * 32 + j3;
  if (tid == 64) PROF_X(2, 5);
  uint32_t t_entry;
  asm volatile("mov.u32 %0, %clock;" : "=r"(t_entry));
  const bool early = cl < N1;
  if (tid == 128) {
    asm volatile("prefetch.tensormap [%0];" ::"l"(&tm_x) : "memory");
    asm volatile("prefetch.tensormap [%0];" ::"l"(&tm_wq) : "memory");
    asm volatile("prefetch.tensormap [%0];" ::"l"(&tm_k) : "memory");
    asm volatile("prefetch.tensormap [%0];" ::"l"(&tm_v) : "memory");
    asm volatile("prefetch.tensormap [%0];" ::"l"(&tm_os) : "memory");
    asm volatile("prefetch.tensormap [%0];" ::"l"(&tm_o) : "memory");
    asm volatile("prefetch.tensormap [%0];" ::"l"(&tm_wo) : "memory");
    asm volatile("prefetch.tensormap [%0];" ::"l"(&tm_out) : "memory");
  }
  if (tid == 0) {
#pragma unroll
    for (int i = 0; i < 90; i++)
      if (bar_cnt(i * 8)) mbar_init(bar + i * 8, bar_cnt(i * 8));
    if (early)
      for (int c = 0; c < 6; c++) asm volatile("mbarrier.arrive.shared::cta.b64 _, [%0], 2;" ::"r"(bar + xf_bar(c)) : "memory");
    asm volatile("fence.mbarrier_init.release.cluster;" ::: "memory");
  }
  if (tid == 96) {
    sts_s32(bar + B_HQ, C_NOP); sts_s32(bar + B_HQ + 4, C_NOP);
    sts_s32(bar + B_NB, 0);
    sts_s32(bar + B_SIDE, -1);
    sts_s32(bar + B_TGT, -1);
    uint32_t t0;
    asm volatile("mov.u32 %0, %globaltimer_lo;" : "=r"(t0));
    sts_s32(bar + B_T0, (int)t0);
    sts_s32(bar + B_ITEMQ, job0);
  }
  __syncthreads();
  asm volatile("barrier.cluster.arrive.relaxed.aligned;" ::: "memory");
  if (tid == 64) PROF_X(2, 6);
  if (wg == 2) asm volatile("setmaxnreg.dec.sync.aligned.u32 40;");
  if (warp == 9 && early) {
    int b, h; job_bh(job0, b, h);
    fence_async_smem();
#pragma unroll 1
    for (int c = 0; c < 6; c++) {
      const uint32_t s = base + q_reg(c) * Q_STAGE, fb = bar + B_QF + 8 * c;
      e_expect(fb, Q_STAGE);
      e_load_2d(s, &tm_x, c * 64, b * SQ, fb);
      e_load_3d(s + 20480, &tm_wq, 0, c * 64, h * 2, fb);
      e_load_3d(s + 28672, &tm_wq, 0, c * 64, h * 2 + 1, fb);
      if (c == 0) PROF_X(2, 15);
    }
  }
  asm volatile("barrier.cluster.wait.aligned;" ::: "memory");
  if (tid == 64) PROF_X(2, 7);

  auto p_any = [&]() -> bool {
    mbar_wait(bar + B_HB, 0);
    return lds_s32(bar + B_DEC) >= 0;
  };
  auto wait_word = [&](const uint32_t a) -> int {
    int v;
    while ((v = __shfl_sync(0xffffffffu, lds_s32(a), 0)) < 0 && !__any_sync(0xffffffffu, deadline_passed())) __nanosleep(50);
    return v;
  };

  if (wg == 2) {
    const uint32_t rbar = mapa(bar, rank ^ 1);
    if (warp == 8) {
      uint64_t pol;
      asm volatile("createpolicy.fractional.L2::evict_first.b64 %0, 1.0;" : "=l"(pol));
      {
        const uint32_t delay = early ? 0 : sc.stag0 + (cl - N1) * sc.stag;
        while (true) {
          uint32_t t1;
          asm volatile("mov.u32 %0, %clock;" : "=r"(t1));
          if (__shfl_sync(0xffffffffu, t1 - t_entry, 0) >= delay) break;
          __nanosleep(100);
        }
      }
      int r = 0;
      for (; r <= 64; r++) {
        const uint32_t ph = r & 1;
        const int it = __shfl_sync(0xffffffffu, lds_s32(bar + B_ITEMQ + (r & 3) * 4), 0);
        if (it < 0) break;
        int b, h; job_bh(it, b, h);
        const int row0 = (b * NH + h) * SK;
        constexpr int SEQ_T[16] = {0, 1, 2, 8, 3, 9, 4, 10, 5, 11, 12, 6, 13, 7, 15, 14};
#pragma unroll
        for (int c = 0; c < 10; c++) {
          if (c < 6 && r == 0 && early) continue;
          if (c >= 6) mbar_wait(bar + B_QE + 8 * (c == 6 ? 0 : c - 5), ph);
          else if (r > 0) {
            if (c == 0) mbar_wait2(bar + B_KE + 48, ph ^ 1, bar + B_PVD + 24, ph ^ 1);
            else if (c == 1) mbar_wait(bar + B_KE + 56, ph ^ 1);
            else mbar_wait(bar + B_PVD + 8 * (c + 2), ph ^ 1);
          }
          const uint32_t s = base + q_reg(c) * Q_STAGE, fb = bar + B_QF + 8 * c;
          PROF_P(c);
          e_arrive2(bar + xf_bar(c), rbar + xf_bar(c));
          e_expect(fb, (c == 9 ? Q_STAGE + 4 : Q_STAGE));
          e_load_2d(s, &tm_x, c * 64, b * SQ, fb);
          if (r == 0 && c == 0) PROF_X(2, 15);
        }
        constexpr int SEQ_W[16] = {B_QE + 40, -1, B_QE + 48, -1, B_QE + 56, -1, B_QE + 64, B_QE + 72, B_KE + 8, B_KE + 16, B_KE + 24,
                                   B_PVD, B_KE + 32, B_PVD + 8, B_KE + 40, B_PVD + 16};
#pragma unroll
        for (int j = 0; j < 16; j++) {
          const int id = SEQ_T[j], t = id & 7;
          if (SEQ_W[j] >= 0) mbar_wait(bar + SEQ_W[j], ph);
          const uint32_t fb = bar + B_KF + 8 * id;
          PROF_P(10 + j);
          e_expect(fb, 16384);
          e_load_3d_hint(base + tab(id >= 8 ? TAB_V : TAB_K, t), id >= 8 ? &tm_v : &tm_k, 0, row0 + t * 64, 0, fb, pol);
        }
      }
      {
        const uint32_t p_full = bar + B_PFULL, p_empty = bar + B_PEMPTY;
        uint32_t st = 0, ph = (r - 1) & 1, oph = ph;
        int o1 = NITEMS, o2 = NITEMS;
        int cn = C_NOP, k0 = 1000;
        const unsigned int target = wait_word(bar + B_TGT);
        unsigned int fv = ~target << 11;
        for (int k = 0; cn >= 0 && k < 200; k++) {
          const int code = cn, h = code & 31;
          const bool mma = code < C_OUT;
          int pg, pj;
          const bool w_share = p_unit((code >> 5) & 63, pg, pj);
          int s0 = NITEMS, s1 = NITEMS;
          if (w_share && mma) {
            s1 = wait_flag(&g_flags[(2 * pg + (lane & 1)) * NH + h], fv, target);
            s0 = __shfl_sync(0xffffffffu, s1, 0); s1 = __shfl_sync(0xffffffffu, s1, 1);
          }
#pragma unroll
          for (int hf = 0; hf < 2; hf++) {
            if (hf == 1) {
              mbar_wait(p_full + 8 * (st ^ 3), ph ^ (st >> 1));
              cn = __shfl_sync(0xffffffffu, lds_s32(bar + B_HQ + ((k + 1) & 3) * 4), 0);
              int g, j;
              if ((unsigned int)cn < C_OUT) {
                if (p_unit((cn >> 5) & 63, g, j)) fv = ld_flag(&g_flags[(2 * g + (lane & 1)) * NH + (cn & 31)]);
                else if (sc.pw & 2)
                  for (int i = 0; i < 4; i++) e_pf_3d(&tm_wo, 0, (cn & 31) * DH + (i >> 1) * 64, j * 2 + (i & 1));
              }
            }
            mbar_wait(p_empty + 8 * st, ph);
            if (k == k0) {
              if (hf == 0) mbar_wait2(bar + B_PVD + 32, (r - 1) & 1, bar + B_KE + 56, (r - 1) & 1);
              else mbar_wait(bar + B_AD, 0);
            }
            if (k == k0 + 1 && hf == 1) mbar_wait(bar + (B_OE + D_OE), (r - 1) & 1);
            const uint32_t s = base + st * P_STAGE, fb = p_full + 8 * st;
            if (hf == 0 || mma) e_arrive2(bar + B_XF + 8 * st, rbar + B_XF + 8 * st);
            e_expect(fb, (mma ? P_STAGE : 0) + (hf ? 0 : 8));
            if (mma) {
              if (w_share) {
                e_load_o(s, &tm_o, o_piece(s0, hf), fb);
                e_load_o(s + 20480, &tm_o, o_piece(s1, hf), fb);
              } else {
                e_load_3d(s + 40960, &tm_wo, 0, h * DH + hf * 64, pj * 2, fb);
                e_load_3d(s + 49152, &tm_wo, 0, h * DH + hf * 64, pj * 2 + 1, fb);
              }
            }
            st = (st + 1) & 3;
          }
          if (code == C_NOP) {
            mbar_wait(p_full + 8 * (st ^ 2), ph ^ 1);
            asm volatile(ELECT_BEGIN "@p mbarrier.arrive.shared::cta.b64 _, [%0], 8;\n@p mbarrier.arrive.shared::cta.b64 _, [%0 + 8], 8;\n}"
                         ::"r"(p_empty + 8 * (st ^ 2)) : "memory");
            if (cn != C_NOP) {
              k0 = k + 1;
              sts_s32(bar + B_DEC, k0 | (cn & 0x80000000));
              arrive_lane0(bar + B_HB);
            }
          } else if (!mma) oph ^= 1;
          if (st == 0) ph ^= 1;
          if (lane < 2) release_slot(o2);
          __syncwarp();
          o2 = o1; o1 = lane ? s1 : s0;
        }
        mbar_wait(bar + B_FIN, 0);
        mbar_wait(bar + B_OF, oph);
        if (lane < 2) release_slot(o2);
      }
    } else if (warp == 11) {
      bool closed = late && rank == 0;
      auto open = [&]() {
        mbar_wait(bar + B_ZF, 0);
        if (lane == 0) asm volatile("st.release.gpu.global.u32 [%0], %1;" ::"l"(&g_hc[(q_own - 30) * 32]), "r"(HC_OPEN) : "memory");
        __syncwarp();
        closed = false;
      };
      int r = 0, side = 0, plan = 0, it;
      unsigned int v;
      for (; r <= 64; r++) {
        it = __shfl_sync(0xffffffffu, lds_s32(bar + B_ITEMQ + (r & 3) * 4), 0);
        if (it < 0) break;
        int b, h; job_bh(it, b, h);
        int n0, n1, sd;
        auto take = [&]() {
          sd = side ^ ((side ? n1 - n0 : n0 - n1) > sc.dbal);
          v = NJOBS;
          if (!late || r + 1 < sc.kl) v = atomicAdd(&g_next[sd * 32], 1u);
        };
        auto send = [&]() {
          v += ncl >> 1;
          if (v >= QLEN - sd && v < NJOBS) { sd ^= 1; v = atomicAdd(&g_next[sd * 32], 1u) + (ncl >> 1); }
          const int nxt = v < QLEN - sd ? sc.order[sd][v] : -1;
          const uint32_t q = B_ITEMQ + ((r + 1) & 3) * 4, lb = mapa(bar, 0);
          st_async(lb + q, nxt, lb + B_QF + 72);
          st_async(rbar + q, nxt, rbar + B_QF + 72);
          if (nxt < 0) {
            plan = atomicAdd(&g_fin, late || nxt < -1 ? 1u : 0x10001u);
            if ((plan & 0xffff) == ncl - 1) { g_next[0] = 0; g_next[32] = 0; g_fin = 0; }
          }
        };
#pragma unroll
        for (int c = 0; c < 10; c++) {
          if (!(c < 6 && r == 0 && early)) {
            mbar_wait(bar + xf_bar(c), (c == 1 || c == 5) ? r & 1 : c >= 6);
            PROF_P(30 + c);
            e_load_3d_mc(base + q_reg(c) * Q_STAGE + 20480 + rank * 8192, &tm_wq, 0, c * 64, h * 2 + rank, bar + B_QF + 8 * c);
          }
          if (rank == 0 && lane == 0) {
            if (c == (LOOKC)) { n0 = __ldcg(&g_next[0]); n1 = __ldcg(&g_next[32]); }
            if (c == (TAKEC) && r > 0) take();
          }
          __syncwarp();
        }
        if (r == 0) PROF_X(2, 12);
        if (r == 0 && rank == 0) side = wait_word(bar + B_SIDE) & 1;
        if (rank == 0 && lane == 0) {
          if (r == 0) take();
          send();
          if (r == 0) PROF_X(2, 13);
        }
        __syncwarp();
        if (closed && r + 1 == sc.kl) open();
        mbar_wait(bar + B_QF + 72, r & 1);
      }
      const int pidx = -2 - it;
      plan = (__shfl_sync(0xffffffffu, plan, 0) >> 16) % 20;
      plan = plan < 10 ? 9 - plan : plan - 10;
      int gs = pidx >= 0 ? 0 : late ? 70 : 71, cur = q_own;
      unsigned int cnt = pidx >= 0 ? ~0u : 0u, rdy = 0, fast = 0;
      const unsigned int target = wait_word(bar + B_TGT);
      auto claim = [&]() -> unsigned int {
        if (closed) open();
        return gs == 70 && lane == 0 ? atomicAdd(&g_hc[(cur - 30) * 32], 1u) : 0u;
      };
      auto gen = [&](unsigned int w, const int k) -> int {
        if (gs < 2) {
          const int q = pidx + 15 * gs;
          if (cnt == 0) {
            if (gs++) gs = late ? 70 : 71; else cnt = ~0u;
            return C_OUT + q;
          }
          if (k == 0) {
            int pg, pj;
            const int d = p_unit(q, pg, pj) ? NH : 0;
            const unsigned int x0 = ld_rlx(&g_fast[pg * NH + lane]), x1 = ld_rlx(&g_fast[pg * NH + d + lane]);
            rdy = __ballot_sync(0xffffffffu, x0 == target && x1 == target);
            if (__popc(rdy) < sc.rs) rdy = 0;
            fast = rdy;
          }
          if (k == 2 && !fast) mbar_wait(bar + B_AD, 0);
          for (int t = k == 2 && !fast ? sc.rf : 1; t > 0 && !rdy; t--) {
            int pg, pj;
            const int d = p_unit(q, pg, pj) ? 2 * NH : 0;
            const unsigned int* f = &g_flags[2 * pg * NH + lane];
            const unsigned int x0 = ld_rlx(f), x1 = ld_rlx(f + NH), x2 = ld_rlx(f + d), x3 = ld_rlx(f + d + NH), tg = target << 11;
            const unsigned int x = (x0 ^ tg) | (x1 ^ tg) | (x2 ^ tg) | (x3 ^ tg);
            rdy = __ballot_sync(0xffffffffu, (x >> 11) == 0) & cnt;
          }
          if (k < 2 && !fast) return C_NOP;
          const int h = gs ? 31 - __clz(rdy ? rdy : cnt) : __ffs(rdy ? rdy : cnt) - 1;
          rdy &= ~(1u << h);
          cnt &= ~(1u << h);
          return q * 32 + h;
        }
        if (gs == 70) {
          w = __shfl_sync(0xffffffffu, w, 0);
          if ((w & 1023) < HC_OPEN + NH) { cnt++; return cur * 32 + (w & 31); }
          gs = 71;
          if (cnt) return (cur == q_own && (w >> 10) == 0 ? C_OUT : C_RED) + cur;
        }
        if (gs == 71) {
          w = 0;
          if (lane < 10) asm volatile("ld.relaxed.gpu.global.u32 %0, [%1];" : "=r"(w) : "l"(&g_hc[lane * 32]) : "memory");
          const int f = (int)(w & 1023) - HC_OPEN, n = (int)(w >> 10) + 1, rem = NH - f;
          const int score = f >= 0 && n < sc.hmax && rem >= sc.hja * n + (k ? sc.hjr : sc.hjb) ? rem * 64 / n : -1;
          const int best = __reduce_max_sync(0xffffffffu, score);
          const unsigned int cand = __ballot_sync(0xffffffffu, score >= 0 && score * 16 >= best * (lane == plan && k == 0 ? sc.htp : sc.hth));
          gs = 72;
          if (k) plan = 31;
          if (cand) {
            cur = 30 + ((cand >> plan) & 1 ? plan : __fns(cand, 0, 1 + cl % __popc(cand)));
            if (lane == 0) asm volatile("atom.acquire.gpu.global.add.u32 %0, [%1], %2;" : "=r"(w) : "l"(&g_hc[(cur - 30) * 32]), "r"(1025u) : "memory");
            w = __shfl_sync(0xffffffffu, w, 0);
            if ((w & 1023) < HC_OPEN + NH) { gs = 70; cnt = 1; return cur * 32 + (w & 31); }
          }
        }
        return -1;
      };
      if (pidx >= 0 && early && r == 1 && rank == 0 && lane == 0) __stcg(&g_fast[job0], target);
      __syncwarp();
      if (pidx >= 0 && pidx < 5)
        for (int i = 0; i < sc.pwo; i++) { e_pf_3d(&tm_wo, 0, i * 64, pidx * 2 + rank); __nanosleep(100); }
      if (rank == 0) {
        mbar_wait(bar + B_KE + 8 * sc.hk, (r - 1) & 1);
        v = claim();
      }
      {
        uint32_t st = 0, ph = (r - 1) & 1, oph = ph, xph = 0;
        int o0 = NITEMS, o1 = NITEMS, o2 = NITEMS, o3 = NITEMS;
        const uint32_t lb = mapa(bar, rank);
        int cn = C_NOP;
        unsigned int fv = ~target << 11;
        for (int k = 0; cn >= 0 && k < 200; k++) {
          unsigned int rc = 0;
          if (lane == 0 && o3 < NITEMS) rc = atomicInc(&g_cons[o3], 2u);
          const int nxt = rank == 0 ? gen(v, k) : 0;
          if (rc == 2u) atomicAnd(&g_busy[o3 >> 5], ~(1u << (o3 & 31)));
          __syncwarp();
          o3 = o2; o2 = o1; o1 = o0;
          const int code = cn, h = code & 31;
          const bool mma = code < C_OUT;
          int pg, pj;
          const bool w_share = p_unit((code >> 5) & 63, pg, pj);
          int s0 = NITEMS;
          if (!w_share && mma) {
            s0 = wait_flag(&g_flags[(2 * pg + rank) * NH + h], fv, target);
            if (k < 69) PROF_X(3, k - 4 - (k > 36));
          }
#pragma unroll
          for (int hf = 0; hf < 2; hf++) {
            if (hf == 1) {
              mbar_wait(bar + B_PFULL + 8 * (st ^ 3), ph ^ (st >> 1));
              cn = __shfl_sync(0xffffffffu, lds_s32(bar + B_HQ + ((k + 1) & 3) * 4), 0);
              int g, j;
              if ((unsigned int)cn < C_OUT) {
                if (!p_unit((cn >> 5) & 63, g, j)) fv = ld_flag(&g_flags[(2 * g + rank) * NH + (cn & 31)]);
                else if (sc.pw & 1) { e_pf_3d(&tm_wo, 0, (cn & 31) * DH, 8 + rank); e_pf_3d(&tm_wo, 0, (cn & 31) * DH + 64, 8 + rank); }
              }
            }
            const uint32_t s = base + st * P_STAGE, fb = bar + B_PFULL + 8 * st;
            if (hf == 0 || mma) {
              mbar_wait(bar + B_XF + 8 * st, (xph >> st) & 1);
              xph ^= 1u << st;
            }
            if (mma) {
              if (w_share) e_load_3d_mc(s + 40960 + rank * 8192, &tm_wo, 0, h * DH + hf * 64, pj * 2 + rank, fb);
              else e_load_o_mc(s + rank * 20480, &tm_o, o_piece(s0, hf), fb);
            }
            if (hf == 0) {
              if (lane == 0) {
                const uint32_t q = rank ? B_DUM : B_HQ + ((k + 2) & 3) * 4;
                st_async(lb + q, nxt, lb + B_PFULL + 8 * st);
                st_async(rbar + q, nxt, rbar + B_PFULL + 8 * st);
              }
              if (rank == 0) v = claim();
              __syncwarp();
            }
            st = (st + 1) & 3;
          }
          if (st == 0) ph ^= 1;
          if (!mma && code != C_NOP) oph ^= 1;
          o0 = s0;
        }
        mbar_wait(bar + B_FIN, 0);
        mbar_wait(bar + B_OF, oph);
        if (lane == 0) { release_slot(o3); release_slot(o2); release_slot(o1); }
      }
    } else if (warp == 9) {
      if (lane == 0) {
        int nrd = 0, r = 0;
        for (; r <= 64; r++) {
          const int it = lds_s32(bar + B_ITEMQ + (r & 3) * 4);
          int b, h; job_bh(it, b, h);
          const int item = b * NH + h;
          const unsigned int old = __ldcg(&g_flags[item]);
          mbar_wait(bar + B_OF, r & 1);
          const int nx = lds_s32(bar + B_ITEMQ + ((r + 1) & 3) * 4);
          const int bs = lds_s32(bar + B_BAD), slot = bs >> 1;
          const int bad = bs & 1;
          for (int hf = 0; hf < 2; hf++) {
            if (hf) mbar_wait(bar + B_OF + D_OF, r & 1);
            PROF_X(2, hf);
            for (int i = 0; i < 4; i++) {
              tma_store_o(&tm_os, i, o_piece(slot, hf), base + QO_OFF + hf * 20480 + i * 5120);
              asm volatile("cp.async.bulk.commit_group;" ::: "memory");
              if (nx >= 0) asm volatile("cp.async.bulk.wait_group.read %0;" ::"n"(OPEND) : "memory");
            }
            if (FASTLAST && nx < 0 && hf == 0) continue;
            asm volatile("cp.async.bulk.wait_group.read 0;" ::: "memory");
            mbar_arrive(bar + B_OE + hf * D_OE);
          }
          asm volatile("cp.async.bulk.wait_group 0;" ::: "memory");
          asm volatile("fence.proxy.async.global;" ::: "memory");
          if (bad) g_redo[blockIdx.x * 72 + nrd++] = item | (slot << 14);
          else publish(item, slot, old);
          PROF_X(2, 2);
          if (nx < 0) break;
        }
        sts_s32(bar + B_NRD, nrd);
        __threadfence();
        mbar_arrive(bar + B_FIN);
        if (p_any()) p_store(base, (r + 1) & 1, &tm_out);
        PROF_X(2, 3);
      }
    } else {
      unsigned int target;
      {
        int b, h; job_bh(job0, b, h);
        target = __ldcg(&g_flags[b * NH + h]);
        uint8_t* p = sc.o + (cl & 3) * 16384 + 1024 + (cl >> 2) * 128 + rank * 65536 * 3, * pp = sc.o + ((size_t)(cl & 31) << 21) + 3968;
        if (lane < 4) lat((lane & 2 ? pp : p) + (lane & 1) * 8192);
        target = ((target >> 11) + 2u) & 0x1fffffu;
        if (lane == 0) sts_s32(bar + B_TGT, target);
        __syncwarp();
        PROF_X(2, 14);
        if (lane == 0 && (rank == 0 || cl < 32)) {
          const bool sd = far_line(p, sc.np);
          if (rank == 0) sts_s32(bar + B_SIDE, (sc.aff & 1) ? sd : cl & 1);
          else __stcg(&g_pol[cl], target * 2 + (sd ^ far_line(pp, sc.np)));
          PROF_X(2, 11);
        }
        __syncwarp();
      }
      bool zf = late;
      auto zero_fill = [&]() {
        int pg, pj; p_unit(q_own, pg, pj);
        uint4* o = sc.out + (pg * 320 + (lane >> 4)) * (DM / 8) + pj * 16 + (lane & 15);
        for (int i = 0; i < 160; i++) {
          __stcg(o + i * (DM / 4), make_uint4(0u, 0u, 0u, 0u));
          if ((i & 7) == 7) __nanosleep(100);
        }
        asm volatile("fence.proxy.async.global;" ::: "memory");
        __threadfence();
        __syncwarp();
        if (lane == 0) asm volatile("mbarrier.arrive.release.cluster.shared::cluster.b64 _, [%0];" ::"r"(mapa(bar + B_ZF, 0)) : "memory");
        zf = false;
      };
      int r = 0;
      for (; r <= 64; r++) {
        if (zf && r + 2 >= sc.kl) zero_fill();
        mbar_wait(bar + B_KE + 8 * sc.pft, r & 1);
        int slot;
        {
          const uint32_t pl = __ldcg(&g_pol[lane]);
          uint32_t skip = (((PAIR_SIDE >> ((lds_s32(bar + B_ITEMQ + (r & 3) * 4) >> 5) & 15)) ^ ((pl >> 1) == target ? pl : 0u)) & 1) ? ~SIDE1_SLOTS : SIDE1_SLOTS;
          if (!(sc.aff & 2)) skip = 0;
          for (uint32_t t = blockIdx.x * 5 + r * 7;; t += 11) {
            uint32_t w;
            asm volatile("ld.relaxed.gpu.global.u32 %0, [%1];" : "=r"(w) : "l"(&g_busy[lane]) : "memory");
            if (__all_sync(0xffffffffu, (w | skip) == ~0u)) skip = 0;
            w |= skip;
            const int n = __popc(~w);
            int pre = n;
#pragma unroll
            for (int o = 1; o < 32; o <<= 1) { const int v = __shfl_up_sync(0xffffffffu, pre, o); if (lane >= o) pre += v; }
            const int k = (int)(t % (uint32_t)max(min(__shfl_sync(0xffffffffu, pre, 31), sc.pfn1), 1));
            int got = -1;
            if (pre - n <= k && k < pre) {
              const int bit = __fns(~w, 0, 1 + k - (pre - n));
              if (!((atomicOr(&g_busy[lane], 1u << bit) >> bit) & 1)) got = lane * 32 + bit;
            }
            slot = __reduce_max_sync(0xffffffffu, got);
            if (slot >= 0) break;
            slot = 0;
            if (deadline_passed()) break;
          }
        }
        mbar_wait(bar + B_LP, r & 1);
        float s[5] = {0.f, 0.f, 0.f, 0.f, 0.f};
#pragma unroll
        for (int w = 0; w < 8; w++) {
          float v0, v1, v2, v3, v4;
          asm volatile("ld.shared.v4.f32 {%0, %1, %2, %3}, [%4];" : "=f"(v0), "=f"(v1), "=f"(v2), "=f"(v3) : "r"(base + LP_OFF + w * 640 + lane * 16));
          asm volatile("ld.shared.f32 %0, [%1];" : "=f"(v4) : "r"(base + LP_OFF + w * 640 + 512 + lane * 4));
          s[0] += v0; s[1] += v1; s[2] += v2; s[3] += v3; s[4] += v4;
        }
        bool bad = false;
#pragma unroll
        for (int k = 0; k < 5; k++) {
          bad |= !(s[k] >= 5.4210109e-20f && s[k] <= 1.2089258e24f);
          const int i = k < 4 ? lane : 32 + (lane >> 2), q = k < 4 ? k : (lane & 3);
          sts_f32(base + LI_OFF + (q * 40 + i) * 4, rcp(s[k]));
        }
        bad = __any_sync(0xffffffffu, bad);
        const int nx = lds_s32(bar + B_ITEMQ + ((r + 1) & 3) * 4);
        if (lane == 0) sts_s32(bar + B_BAD, (int)bad | (slot << 1));
        if (bad && lane == 0) sts_s32(bar + B_NB, 1);
        __syncwarp();
        if (lane == 0) mbar_arrive(bar + B_LI);
        if (__shfl_sync(0xffffffffu, nx, 0) < 0) break;
      }
      if (zf) zero_fill();
    }
    __syncwarp();
  } else {
    asm volatile("setmaxnreg.inc.sync.aligned.u32 232;");
    float accS[80], accO[80];
    PROF_CLR(); PROF_G(60); PROF_T(61);
    const int nr = a_role(base, wg, sc, accS, accO);
    int nrd = 0;
    if (__shfl_sync(0xffffffffu, lds_s32(bar + B_NB), 0)) {
      mbar_wait(bar + B_FIN, 0);
      nrd = min(__shfl_sync(0xffffffffu, lds_s32(bar + B_NRD), 0), 65);
    }
    for (int i = 0; i < nrd; i++) {
      const int ent = __ldcg(&g_redo[blockIdx.x * 72 + i]), item = ent & (NITEMS - 1), slot = (ent >> 14) & 0x3ff;
      slow_item(sc.o + 4096 + (size_t)o_piece(slot, 0) * 8192, (o_piece(slot, 1) - o_piece(slot, 0)) * 8192, sc.kp + (size_t)item * SK * DH, sc.vp + (size_t)item * SK * DH,
                sc.xp + (size_t)(item >> 5) * SQ * DM, sc.wp + (item & 31) * DH, 20);
      asm volatile("fence.proxy.async.global;" ::: "memory");
      __syncwarp();
      if (lane == 0) {
        __threadfence();
        if (((atomicAdd(&g_redo[blockIdx.x * 72 + i], NITEMS) >> 10) & 15) == 7) {
          __threadfence();
          publish(item, slot, __ldcg(&g_flags[item]));
        }
      }
      __syncwarp();
    }
    p_role(base, wg, nr & 1, accS, accO);
    PROF_DUMP();
  }
  cluster_sync();
  if (tid == 64) PROF_X(2, 9);
}

typedef CUresult (*EncodeFn)(CUtensorMap*, CUtensorMapDataType, cuuint32_t, void*, const cuuint64_t*, const cuuint64_t*,
                             const cuuint32_t*, const cuuint32_t*, CUtensorMapInterleave, CUtensorMapSwizzle,
                             CUtensorMapL2promotion, CUtensorMapFloatOOBfill);

void make_map(EncodeFn enc, CUtensorMap* m, const void* ptr, int rank, const cuuint64_t* dims, const cuuint64_t* strides,
              const cuuint32_t* box, CUtensorMapL2promotion promo) {
  cuuint32_t es[4] = {1, 1, 1, 1};
  enc(m, CU_TENSOR_MAP_DATA_TYPE_BFLOAT16, rank, const_cast<void*>(ptr), dims, strides, box, es, CU_TENSOR_MAP_INTERLEAVE_NONE,
      CU_TENSOR_MAP_SWIZZLE_128B, promo, CU_TENSOR_MAP_FLOAT_OOB_FILL_NONE);
}

}

extern "C" void kernel_launch(void* const* d_in, const int* in_sizes, int n_in, void* d_out, int out_size) {
  (void)in_sizes; (void)n_in; (void)out_size;
  static EncodeFn enc = nullptr;
  static void* o_ptr = nullptr;
  if (!enc) {
    void* fn = nullptr;
    cudaDriverEntryPointQueryResult qr;
    cudaGetDriverEntryPoint("cuTensorMapEncodeTiled", &fn, cudaEnableDefault, &qr);
    enc = (EncodeFn)fn;
    cudaGetSymbolAddress(&o_ptr, g_O);
    o_ptr = (void*)(((uintptr_t)o_ptr + (2 << 20) - 1) & ~(uintptr_t)((2 << 20) - 1));
    cudaFuncSetAttribute(fused_kernel, cudaFuncAttributeMaxDynamicSharedMemorySize, SMEM_BYTES);
  }
  CUtensorMap tm_x, tm_wq, tm_k, tm_v, tm_o, tm_wo, tm_out, tm_os;
  {
    cuuint64_t d[2] = {DM, (cuuint64_t)NB * SQ}, s[1] = {DM * 2};
    cuuint32_t bx[2] = {64, SQ};
    make_map(enc, &tm_x, d_in[0], 2, d, s, bx, CU_TENSOR_MAP_L2_PROMOTION_L2_128B);
    make_map(enc, &tm_out, d_out, 2, d, s, bx, CU_TENSOR_MAP_L2_PROMOTION_NONE);
  }
  {
    cuuint64_t d[3] = {64, (cuuint64_t)NB * NH * SK, 2}, s[2] = {DH * 2, 128};
    cuuint32_t bx[3] = {64, 64, 2};
    make_map(enc, &tm_k, d_in[1], 3, d, s, bx, CU_TENSOR_MAP_L2_PROMOTION_L2_128B);
    make_map(enc, &tm_v, d_in[2], 3, d, s, bx, CU_TENSOR_MAP_L2_PROMOTION_L2_128B);
  }
  {
    cuuint64_t d[3] = {64, DM, (cuuint64_t)NH * 2}, s[2] = {(cuuint64_t)NH * DH * 2, 128};
    cuuint32_t bx[3] = {64, 64, 1};
    make_map(enc, &tm_wq, d_in[3], 3, d, s, bx, CU_TENSOR_MAP_L2_PROMOTION_L2_256B);
  }
  {
    cuuint64_t d[3] = {64, (cuuint64_t)NH * DH, DM / 64}, s[2] = {DM * 2, 128};
    cuuint32_t bx[3] = {64, 64, 1};
    make_map(enc, &tm_wo, d_in[4], 3, d, s, bx, CU_TENSOR_MAP_L2_PROMOTION_L2_256B);
  }
  {
    cuuint64_t d[4] = {64, 40, 4, (cuuint64_t)NITEMS * 8}, s[3] = {128, 16384, 8192};
    cuuint32_t bl[4] = {64, 40, 4, 1}, bs[4] = {64, 40, 1, 1};
    make_map(enc, &tm_o, (uint8_t*)o_ptr + 4096, 4, d, s, bl, CU_TENSOR_MAP_L2_PROMOTION_L2_128B);
    make_map(enc, &tm_os, (uint8_t*)o_ptr + 4096, 4, d, s, bs, CU_TENSOR_MAP_L2_PROMOTION_NONE);
  }
  Sched sc;
  sc.kl = 9;
  sc.zero = 0; sc.stag = 360; sc.stag0 = 1500; sc.pfn1 = 24; sc.pft = 2;
  sc.hmax = 6; sc.hja = 1; sc.hjb = 1; sc.hjr = 2; sc.hk = 4;
  sc.hth = 12; sc.htp = 9;
  sc.rs = 1; sc.aff = 3; sc.dbal = 6; sc.np = 3; sc.pw = 0; sc.pwo = 8; sc.rf = 8;
  sc.kp = (const __nv_bfloat16*)d_in[1]; sc.vp = (const __nv_bfloat16*)d_in[2];
  sc.xp = (const __nv_bfloat16*)d_in[0]; sc.wp = (const __nv_bfloat16*)d_in[3]; sc.out = (uint4*)d_out; sc.o = (uint8_t*)o_ptr;
  {
    int need[NJOBS];
    for (int j = 0; j < NJOBS; j++) {
      const int g = j >> 6, h = j & 31;
      need[j] = g < 6 ? 22000 + (g >= 3 ? 64 - h : h) * 2620 : 160000 + h * 1500;
    }
    for (int j = 0; j < NJOBS; j++) {
      const int sd = (PAIR_SIDE >> (j >> 5)) & 1;
      int r = 0;
      for (int i = 0; i < NJOBS; i++) r += ((PAIR_SIDE >> (i >> 5)) & 1) == sd && (need[i] < need[j] || (need[i] == need[j] && i < j));
      sc.order[sd][r < 33 ? r : r + 8 - sd] = (short)j;
    }
    for (int i = 0; i < 8; i++) sc.order[0][33 + i] = -2 - (int)((0xeba43210u >> (4 * i)) & 15);
    for (int i = 0; i < 7; i++) sc.order[1][33 + i] = -2 - (int)((0xdc98765u >> (4 * i)) & 15);
    sc.order[1][QLEN - 1] = -1;
  }
  fused_kernel<<<132, 384, SMEM_BYTES>>>(tm_x, tm_wq, tm_k, tm_v, tm_o, tm_wo, tm_out, tm_os, sc);
}
```
